```python
import torch

def _softmax(x, axis=-1):
    return torch.softmax(x, dim=axis)

def _gelu(x):
    return torch.nn.functional.gelu(x, approximate='tanh')

def _silu(x):
    return torch.nn.functional.silu(x)

def _sigmoid(x):
    return torch.sigmoid(x)

def _layernorm(x, axis=-1, eps=1e-05):
    m = x.mean(dim=axis, keepdim=True)
    v = x.var(dim=axis, keepdim=True, unbiased=False)
    return (x - m) / torch.sqrt(v + eps)

def _scatter_add(tgt, idx, src, axis=0):
    return tgt.clone().index_add_(axis, idx, src)

def _segment_sum(src, seg, n):
    out = torch.zeros((n,) + src.shape[1:], dtype=src.dtype)
    return out.index_add_(0, seg, src)

def _pad(x, pw):
    flat = tuple((v for pair in reversed(pw) for v in pair))
    return torch.nn.functional.pad(x, flat)
kernel_name = 'adaLN_cond__ssm_conv_h3__mixer_gmlp__prompt'

def setup_inputs():

    _w = lambda a: (lambda t: t.to(torch.bfloat16) if t.is_floating_point() else t)(torch.as_tensor(a))

    def _A_setup():
        B, S, D = (1, 2048, 640)
        ks = 4
        return {'q': _w((lambda *s: torch.randn(*s, dtype=torch.bfloat16) * 0.05)(B, S, D)), 'k': _w((lambda *s: torch.randn(*s, dtype=torch.bfloat16) * 1.6)(B, S, D)), 'v': _w((lambda *s: torch.randn(*s, dtype=torch.bfloat16) * 1.6)(B, S, D)), 'shift_k': _w((lambda *s: torch.randn(*s, dtype=torch.bfloat16) * 1.6)(D, ks) * 0.5), 'ssm_k': _w((lambda *s: torch.randn(*s, dtype=torch.bfloat16) * 1.6)(D, S) * (1.0 / S ** 0.5)), 'ssm_D': _w((lambda *s: torch.randn(*s, dtype=torch.bfloat16) * 1.6)(D))}
    _A_in = _A_setup()

    def _B_setup():
        B, S, D, F = (1, 2048, 640, 1728)
        Fh = F // 2
        return {'x': _w((lambda *s: torch.randn(*s, dtype=torch.bfloat16) * 0.05)(B, S, D)), 'w_in': _w((lambda *s: torch.randn(*s, dtype=torch.bfloat16) * 0.8)(D, 2 * Fh)), 'w_sp': _w(0.01 * (lambda *s: torch.randn(*s, dtype=torch.bfloat16) * 0.8)(S, S)), 'b_sp': _w(1.0 + 0.01 * (lambda *s: torch.randn(*s, dtype=torch.bfloat16) * 0.1)(S)), 'w_out': _w((lambda *s: torch.randn(*s, dtype=torch.bfloat16) * 0.1)(Fh, D))}
    _B_in = _B_setup()
    return {'A_q': _A_in['q'], 'A_k': _A_in['k'], 'A_v': _A_in['v'], 'A_shift_k': _A_in['shift_k'], 'A_ssm_k': _A_in['ssm_k'], 'A_ssm_D': _A_in['ssm_D'], 'B_x': _B_in['x'], 'B_w_in': _B_in['w_in'], 'B_w_sp': _B_in['w_sp'], 'B_b_sp': _B_in['b_sp'], 'B_w_out': _B_in['w_out'], 'c': _w((lambda *s: torch.randn(*s, dtype=torch.bfloat16) * 0.1)(1, 640) * 8.0), 'w_mod': _w((lambda *s: torch.randn(*s, dtype=torch.bfloat16) * 0.1)(640, 6 * 640) * 640 ** (-0.5) * 8.0)}

def reference(A_q, A_k, A_v, A_shift_k, A_ssm_k, A_ssm_D, B_x, B_w_in, B_w_sp, B_b_sp, B_w_out, c, w_mod):

    def _A_ref(q, k, v, shift_k, ssm_k, ssm_D):
        B, S, D = q.shape
        ks = shift_k.shape[-1]
        k_pad = _pad(k, ((0, 0), (ks - 1, 0), (0, 0)))
        k_shift = torch.zeros_like(k)
        for t in range(ks):
            k_shift = k_shift + k_pad[:, t:t + S, :] * shift_k[:, ks - 1 - t][None, None, :]
        kv = k_shift * v
        L = 2 * S
        kv_pad = _pad(kv, ((0, 0), (0, S), (0, 0)))
        kf_pad = _pad(ssm_k, ((0, 0), (0, S)))
        kv_f = (lambda x, axes=(-2, -1): torch.fft.rfft2(x.float(), dim=axes))(kv_pad[:, None, :, :], axes=(1, 2))
        kf_f = (lambda x, axes=(-2, -1): torch.fft.rfft2(x.float(), dim=axes))(kf_pad[:, None, :], axes=(1, 2))
        kf_f = (lambda x, *d: x.permute(*d))(kf_f, 1, 2, 0)
        y_f = kv_f * kf_f[None, :, :, :]
        y = (lambda x, s, axes=(-2, -1): torch.fft.irfft2(x, s=s, dim=axes).to(torch.bfloat16))(y_f, (1, L), axes=(1, 2))[:, 0, :S, :]
        y = y + kv * ssm_D[None, None, :]
        return q * y

    def _B_ref(x, w_in, w_sp, b_sp, w_out):
        B, S, D = x.shape
        F = w_in.shape[-1]
        Fh = F // 2
        z = _gelu(torch.einsum('bsd,df->bsf', x, w_in))
        z1 = z[..., :Fh].clone()
        z2 = _layernorm(z[..., Fh:], axis=-1)
        g = torch.einsum('ts,bsf->btf', w_sp, z2) + b_sp[None, :, None]
        return torch.einsum('bsf,fd->bsd', z1 * g, w_out)
    x = A_q
    mod = (_silu(c) @ w_mod).reshape(c.shape[0], 6, 1, -1)
    sa, ca, ga, sb, cb, gb = (mod[:, 0].clone(), mod[:, 1].clone(), mod[:, 2].clone(), mod[:, 3].clone(), mod[:, 4].clone(), mod[:, 5].clone())
    h = _layernorm(x, axis=-1) * (1 + ca) + sa
    x = x + ga * _A_ref(h, A_k, A_v, A_shift_k, A_ssm_k, A_ssm_D)
    h = _layernorm(x, axis=-1) * (1 + cb) + sb
    x = x + gb * _B_ref(h, B_w_in, B_w_sp, B_b_sp, B_w_out)
    return x
```

```cpp
#include <cuda_runtime.h>
#include <cuda.h>
#include <cuda_bf16.h>
#include <stdint.h>
#include <string.h>
#include <stddef.h>

#define SEQ0 0x3332313021110120ull
#define SEQ1 0x0423130322120234ull
#define SEQ2 0xffffffffffff2414ull
#define T_W0 1200
#define W_GAP 600
#define PACE_1 2200
#define PACE_D 400
#define PACE_W 600
#define T_SPARE 9000
#define PF_GAP 1500
#define STAG_Z 0
#define PROFWG 1
#define EARLY_A 0
#define EARLY_B 0
#define CONV_MUTEX 1
#define QPOS 0
#define GATE7 -1
#define ALIGN2 1
#define LATEFO 1
#define WARM_RND -1
#define STOP_AFTER 99

namespace {

template<int N> struct WRS;
template<> struct WRS<16> { static __device__ __forceinline__ void mma(float* d, const uint32_t* a, uint64_t db) {
  asm volatile("wgmma.mma_async.sync.aligned.m64n16k16.f32.bf16.bf16 {%0,%1,%2,%3,%4,%5,%6,%7}, {%8,%9,%10,%11}, %12, 1, 1, 1, 0;"
    : "+f"(d[0]),"+f"(d[1]),"+f"(d[2]),"+f"(d[3]),"+f"(d[4]),"+f"(d[5]),"+f"(d[6]),"+f"(d[7])
    : "r"(a[0]), "r"(a[1]), "r"(a[2]), "r"(a[3]), "l"(db)); } };
template<> struct WRS<32> { static __device__ __forceinline__ void mma(float* d, const uint32_t* a, uint64_t db) {
  asm volatile("wgmma.mma_async.sync.aligned.m64n32k16.f32.bf16.bf16 {%0,%1,%2,%3,%4,%5,%6,%7,%8,%9,%10,%11,%12,%13,%14,%15}, {%16,%17,%18,%19}, %20, 1, 1, 1, 0;"
    : "+f"(d[0]),"+f"(d[1]),"+f"(d[2]),"+f"(d[3]),"+f"(d[4]),"+f"(d[5]),"+f"(d[6]),"+f"(d[7]),"+f"(d[8]),"+f"(d[9]),"+f"(d[10]),"+f"(d[11]),"+f"(d[12]),"+f"(d[13]),"+f"(d[14]),"+f"(d[15])
    : "r"(a[0]), "r"(a[1]), "r"(a[2]), "r"(a[3]), "l"(db)); } };
template<> struct WRS<48> { static __device__ __forceinline__ void mma(float* d, const uint32_t* a, uint64_t db) {
  asm volatile("wgmma.mma_async.sync.aligned.m64n48k16.f32.bf16.bf16 {%0,%1,%2,%3,%4,%5,%6,%7,%8,%9,%10,%11,%12,%13,%14,%15,%16,%17,%18,%19,%20,%21,%22,%23}, {%24,%25,%26,%27}, %28, 1, 1, 1, 0;"
    : "+f"(d[0]),"+f"(d[1]),"+f"(d[2]),"+f"(d[3]),"+f"(d[4]),"+f"(d[5]),"+f"(d[6]),"+f"(d[7]),"+f"(d[8]),"+f"(d[9]),"+f"(d[10]),"+f"(d[11]),"+f"(d[12]),"+f"(d[13]),"+f"(d[14]),"+f"(d[15]),"+f"(d[16]),"+f"(d[17]),"+f"(d[18]),"+f"(d[19]),"+f"(d[20]),"+f"(d[21]),"+f"(d[22]),"+f"(d[23])
    : "r"(a[0]), "r"(a[1]), "r"(a[2]), "r"(a[3]), "l"(db)); } };
template<> struct WRS<64> { static __device__ __forceinline__ void mma(float* d, const uint32_t* a, uint64_t db) {
  asm volatile("wgmma.mma_async.sync.aligned.m64n64k16.f32.bf16.bf16 {%0,%1,%2,%3,%4,%5,%6,%7,%8,%9,%10,%11,%12,%13,%14,%15,%16,%17,%18,%19,%20,%21,%22,%23,%24,%25,%26,%27,%28,%29,%30,%31}, {%32,%33,%34,%35}, %36, 1, 1, 1, 0;"
    : "+f"(d[0]),"+f"(d[1]),"+f"(d[2]),"+f"(d[3]),"+f"(d[4]),"+f"(d[5]),"+f"(d[6]),"+f"(d[7]),"+f"(d[8]),"+f"(d[9]),"+f"(d[10]),"+f"(d[11]),"+f"(d[12]),"+f"(d[13]),"+f"(d[14]),"+f"(d[15]),"+f"(d[16]),"+f"(d[17]),"+f"(d[18]),"+f"(d[19]),"+f"(d[20]),"+f"(d[21]),"+f"(d[22]),"+f"(d[23]),"+f"(d[24]),"+f"(d[25]),"+f"(d[26]),"+f"(d[27]),"+f"(d[28]),"+f"(d[29]),"+f"(d[30]),"+f"(d[31])
    : "r"(a[0]), "r"(a[1]), "r"(a[2]), "r"(a[3]), "l"(db)); } };
template<> struct WRS<80> { static __device__ __forceinline__ void mma(float* d, const uint32_t* a, uint64_t db) {
  asm volatile("wgmma.mma_async.sync.aligned.m64n80k16.f32.bf16.bf16 {%0,%1,%2,%3,%4,%5,%6,%7,%8,%9,%10,%11,%12,%13,%14,%15,%16,%17,%18,%19,%20,%21,%22,%23,%24,%25,%26,%27,%28,%29,%30,%31,%32,%33,%34,%35,%36,%37,%38,%39}, {%40,%41,%42,%43}, %44, 1, 1, 1, 0;"
    : "+f"(d[0]),"+f"(d[1]),"+f"(d[2]),"+f"(d[3]),"+f"(d[4]),"+f"(d[5]),"+f"(d[6]),"+f"(d[7]),"+f"(d[8]),"+f"(d[9]),"+f"(d[10]),"+f"(d[11]),"+f"(d[12]),"+f"(d[13]),"+f"(d[14]),"+f"(d[15]),"+f"(d[16]),"+f"(d[17]),"+f"(d[18]),"+f"(d[19]),"+f"(d[20]),"+f"(d[21]),"+f"(d[22]),"+f"(d[23]),"+f"(d[24]),"+f"(d[25]),"+f"(d[26]),"+f"(d[27]),"+f"(d[28]),"+f"(d[29]),"+f"(d[30]),"+f"(d[31]),"+f"(d[32]),"+f"(d[33]),"+f"(d[34]),"+f"(d[35]),"+f"(d[36]),"+f"(d[37]),"+f"(d[38]),"+f"(d[39])
    : "r"(a[0]), "r"(a[1]), "r"(a[2]), "r"(a[3]), "l"(db)); } };
template<> struct WRS<96> { static __device__ __forceinline__ void mma(float* d, const uint32_t* a, uint64_t db) {
  asm volatile("wgmma.mma_async.sync.aligned.m64n96k16.f32.bf16.bf16 {%0,%1,%2,%3,%4,%5,%6,%7,%8,%9,%10,%11,%12,%13,%14,%15,%16,%17,%18,%19,%20,%21,%22,%23,%24,%25,%26,%27,%28,%29,%30,%31,%32,%33,%34,%35,%36,%37,%38,%39,%40,%41,%42,%43,%44,%45,%46,%47}, {%48,%49,%50,%51}, %52, 1, 1, 1, 0;"
    : "+f"(d[0]),"+f"(d[1]),"+f"(d[2]),"+f"(d[3]),"+f"(d[4]),"+f"(d[5]),"+f"(d[6]),"+f"(d[7]),"+f"(d[8]),"+f"(d[9]),"+f"(d[10]),"+f"(d[11]),"+f"(d[12]),"+f"(d[13]),"+f"(d[14]),"+f"(d[15]),"+f"(d[16]),"+f"(d[17]),"+f"(d[18]),"+f"(d[19]),"+f"(d[20]),"+f"(d[21]),"+f"(d[22]),"+f"(d[23]),"+f"(d[24]),"+f"(d[25]),"+f"(d[26]),"+f"(d[27]),"+f"(d[28]),"+f"(d[29]),"+f"(d[30]),"+f"(d[31]),"+f"(d[32]),"+f"(d[33]),"+f"(d[34]),"+f"(d[35]),"+f"(d[36]),"+f"(d[37]),"+f"(d[38]),"+f"(d[39]),"+f"(d[40]),"+f"(d[41]),"+f"(d[42]),"+f"(d[43]),"+f"(d[44]),"+f"(d[45]),"+f"(d[46]),"+f"(d[47])
    : "r"(a[0]), "r"(a[1]), "r"(a[2]), "r"(a[3]), "l"(db)); } };
template<> struct WRS<112> { static __device__ __forceinline__ void mma(float* d, const uint32_t* a, uint64_t db) {
  asm volatile("wgmma.mma_async.sync.aligned.m64n112k16.f32.bf16.bf16 {%0,%1,%2,%3,%4,%5,%6,%7,%8,%9,%10,%11,%12,%13,%14,%15,%16,%17,%18,%19,%20,%21,%22,%23,%24,%25,%26,%27,%28,%29,%30,%31,%32,%33,%34,%35,%36,%37,%38,%39,%40,%41,%42,%43,%44,%45,%46,%47,%48,%49,%50,%51,%52,%53,%54,%55}, {%56,%57,%58,%59}, %60, 1, 1, 1, 0;"
    : "+f"(d[0]),"+f"(d[1]),"+f"(d[2]),"+f"(d[3]),"+f"(d[4]),"+f"(d[5]),"+f"(d[6]),"+f"(d[7]),"+f"(d[8]),"+f"(d[9]),"+f"(d[10]),"+f"(d[11]),"+f"(d[12]),"+f"(d[13]),"+f"(d[14]),"+f"(d[15]),"+f"(d[16]),"+f"(d[17]),"+f"(d[18]),"+f"(d[19]),"+f"(d[20]),"+f"(d[21]),"+f"(d[22]),"+f"(d[23]),"+f"(d[24]),"+f"(d[25]),"+f"(d[26]),"+f"(d[27]),"+f"(d[28]),"+f"(d[29]),"+f"(d[30]),"+f"(d[31]),"+f"(d[32]),"+f"(d[33]),"+f"(d[34]),"+f"(d[35]),"+f"(d[36]),"+f"(d[37]),"+f"(d[38]),"+f"(d[39]),"+f"(d[40]),"+f"(d[41]),"+f"(d[42]),"+f"(d[43]),"+f"(d[44]),"+f"(d[45]),"+f"(d[46]),"+f"(d[47]),"+f"(d[48]),"+f"(d[49]),"+f"(d[50]),"+f"(d[51]),"+f"(d[52]),"+f"(d[53]),"+f"(d[54]),"+f"(d[55])
    : "r"(a[0]), "r"(a[1]), "r"(a[2]), "r"(a[3]), "l"(db)); } };
template<> struct WRS<128> { static __device__ __forceinline__ void mma(float* d, const uint32_t* a, uint64_t db) {
  asm volatile("wgmma.mma_async.sync.aligned.m64n128k16.f32.bf16.bf16 {%0,%1,%2,%3,%4,%5,%6,%7,%8,%9,%10,%11,%12,%13,%14,%15,%16,%17,%18,%19,%20,%21,%22,%23,%24,%25,%26,%27,%28,%29,%30,%31,%32,%33,%34,%35,%36,%37,%38,%39,%40,%41,%42,%43,%44,%45,%46,%47,%48,%49,%50,%51,%52,%53,%54,%55,%56,%57,%58,%59,%60,%61,%62,%63}, {%64,%65,%66,%67}, %68, 1, 1, 1, 0;"
    : "+f"(d[0]),"+f"(d[1]),"+f"(d[2]),"+f"(d[3]),"+f"(d[4]),"+f"(d[5]),"+f"(d[6]),"+f"(d[7]),"+f"(d[8]),"+f"(d[9]),"+f"(d[10]),"+f"(d[11]),"+f"(d[12]),"+f"(d[13]),"+f"(d[14]),"+f"(d[15]),"+f"(d[16]),"+f"(d[17]),"+f"(d[18]),"+f"(d[19]),"+f"(d[20]),"+f"(d[21]),"+f"(d[22]),"+f"(d[23]),"+f"(d[24]),"+f"(d[25]),"+f"(d[26]),"+f"(d[27]),"+f"(d[28]),"+f"(d[29]),"+f"(d[30]),"+f"(d[31]),"+f"(d[32]),"+f"(d[33]),"+f"(d[34]),"+f"(d[35]),"+f"(d[36]),"+f"(d[37]),"+f"(d[38]),"+f"(d[39]),"+f"(d[40]),"+f"(d[41]),"+f"(d[42]),"+f"(d[43]),"+f"(d[44]),"+f"(d[45]),"+f"(d[46]),"+f"(d[47]),"+f"(d[48]),"+f"(d[49]),"+f"(d[50]),"+f"(d[51]),"+f"(d[52]),"+f"(d[53]),"+f"(d[54]),"+f"(d[55]),"+f"(d[56]),"+f"(d[57]),"+f"(d[58]),"+f"(d[59]),"+f"(d[60]),"+f"(d[61]),"+f"(d[62]),"+f"(d[63])
    : "r"(a[0]), "r"(a[1]), "r"(a[2]), "r"(a[3]), "l"(db)); } };
template<> struct WRS<144> { static __device__ __forceinline__ void mma(float* d, const uint32_t* a, uint64_t db) {
  asm volatile("wgmma.mma_async.sync.aligned.m64n144k16.f32.bf16.bf16 {%0,%1,%2,%3,%4,%5,%6,%7,%8,%9,%10,%11,%12,%13,%14,%15,%16,%17,%18,%19,%20,%21,%22,%23,%24,%25,%26,%27,%28,%29,%30,%31,%32,%33,%34,%35,%36,%37,%38,%39,%40,%41,%42,%43,%44,%45,%46,%47,%48,%49,%50,%51,%52,%53,%54,%55,%56,%57,%58,%59,%60,%61,%62,%63,%64,%65,%66,%67,%68,%69,%70,%71}, {%72,%73,%74,%75}, %76, 1, 1, 1, 0;"
    : "+f"(d[0]),"+f"(d[1]),"+f"(d[2]),"+f"(d[3]),"+f"(d[4]),"+f"(d[5]),"+f"(d[6]),"+f"(d[7]),"+f"(d[8]),"+f"(d[9]),"+f"(d[10]),"+f"(d[11]),"+f"(d[12]),"+f"(d[13]),"+f"(d[14]),"+f"(d[15]),"+f"(d[16]),"+f"(d[17]),"+f"(d[18]),"+f"(d[19]),"+f"(d[20]),"+f"(d[21]),"+f"(d[22]),"+f"(d[23]),"+f"(d[24]),"+f"(d[25]),"+f"(d[26]),"+f"(d[27]),"+f"(d[28]),"+f"(d[29]),"+f"(d[30]),"+f"(d[31]),"+f"(d[32]),"+f"(d[33]),"+f"(d[34]),"+f"(d[35]),"+f"(d[36]),"+f"(d[37]),"+f"(d[38]),"+f"(d[39]),"+f"(d[40]),"+f"(d[41]),"+f"(d[42]),"+f"(d[43]),"+f"(d[44]),"+f"(d[45]),"+f"(d[46]),"+f"(d[47]),"+f"(d[48]),"+f"(d[49]),"+f"(d[50]),"+f"(d[51]),"+f"(d[52]),"+f"(d[53]),"+f"(d[54]),"+f"(d[55]),"+f"(d[56]),"+f"(d[57]),"+f"(d[58]),"+f"(d[59]),"+f"(d[60]),"+f"(d[61]),"+f"(d[62]),"+f"(d[63]),"+f"(d[64]),"+f"(d[65]),"+f"(d[66]),"+f"(d[67]),"+f"(d[68]),"+f"(d[69]),"+f"(d[70]),"+f"(d[71])
    : "r"(a[0]), "r"(a[1]), "r"(a[2]), "r"(a[3]), "l"(db)); } };
template<> struct WRS<160> { static __device__ __forceinline__ void mma(float* d, const uint32_t* a, uint64_t db) {
  asm volatile("wgmma.mma_async.sync.aligned.m64n160k16.f32.bf16.bf16 {%0,%1,%2,%3,%4,%5,%6,%7,%8,%9,%10,%11,%12,%13,%14,%15,%16,%17,%18,%19,%20,%21,%22,%23,%24,%25,%26,%27,%28,%29,%30,%31,%32,%33,%34,%35,%36,%37,%38,%39,%40,%41,%42,%43,%44,%45,%46,%47,%48,%49,%50,%51,%52,%53,%54,%55,%56,%57,%58,%59,%60,%61,%62,%63,%64,%65,%66,%67,%68,%69,%70,%71,%72,%73,%74,%75,%76,%77,%78,%79}, {%80,%81,%82,%83}, %84, 1, 1, 1, 0;"
    : "+f"(d[0]),"+f"(d[1]),"+f"(d[2]),"+f"(d[3]),"+f"(d[4]),"+f"(d[5]),"+f"(d[6]),"+f"(d[7]),"+f"(d[8]),"+f"(d[9]),"+f"(d[10]),"+f"(d[11]),"+f"(d[12]),"+f"(d[13]),"+f"(d[14]),"+f"(d[15]),"+f"(d[16]),"+f"(d[17]),"+f"(d[18]),"+f"(d[19]),"+f"(d[20]),"+f"(d[21]),"+f"(d[22]),"+f"(d[23]),"+f"(d[24]),"+f"(d[25]),"+f"(d[26]),"+f"(d[27]),"+f"(d[28]),"+f"(d[29]),"+f"(d[30]),"+f"(d[31]),"+f"(d[32]),"+f"(d[33]),"+f"(d[34]),"+f"(d[35]),"+f"(d[36]),"+f"(d[37]),"+f"(d[38]),"+f"(d[39]),"+f"(d[40]),"+f"(d[41]),"+f"(d[42]),"+f"(d[43]),"+f"(d[44]),"+f"(d[45]),"+f"(d[46]),"+f"(d[47]),"+f"(d[48]),"+f"(d[49]),"+f"(d[50]),"+f"(d[51]),"+f"(d[52]),"+f"(d[53]),"+f"(d[54]),"+f"(d[55]),"+f"(d[56]),"+f"(d[57]),"+f"(d[58]),"+f"(d[59]),"+f"(d[60]),"+f"(d[61]),"+f"(d[62]),"+f"(d[63]),"+f"(d[64]),"+f"(d[65]),"+f"(d[66]),"+f"(d[67]),"+f"(d[68]),"+f"(d[69]),"+f"(d[70]),"+f"(d[71]),"+f"(d[72]),"+f"(d[73]),"+f"(d[74]),"+f"(d[75]),"+f"(d[76]),"+f"(d[77]),"+f"(d[78]),"+f"(d[79])
    : "r"(a[0]), "r"(a[1]), "r"(a[2]), "r"(a[3]), "l"(db)); } };
template<> struct WRS<176> { static __device__ __forceinline__ void mma(float* d, const uint32_t* a, uint64_t db) {
  asm volatile("wgmma.mma_async.sync.aligned.m64n176k16.f32.bf16.bf16 {%0,%1,%2,%3,%4,%5,%6,%7,%8,%9,%10,%11,%12,%13,%14,%15,%16,%17,%18,%19,%20,%21,%22,%23,%24,%25,%26,%27,%28,%29,%30,%31,%32,%33,%34,%35,%36,%37,%38,%39,%40,%41,%42,%43,%44,%45,%46,%47,%48,%49,%50,%51,%52,%53,%54,%55,%56,%57,%58,%59,%60,%61,%62,%63,%64,%65,%66,%67,%68,%69,%70,%71,%72,%73,%74,%75,%76,%77,%78,%79,%80,%81,%82,%83,%84,%85,%86,%87}, {%88,%89,%90,%91}, %92, 1, 1, 1, 0;"
    : "+f"(d[0]),"+f"(d[1]),"+f"(d[2]),"+f"(d[3]),"+f"(d[4]),"+f"(d[5]),"+f"(d[6]),"+f"(d[7]),"+f"(d[8]),"+f"(d[9]),"+f"(d[10]),"+f"(d[11]),"+f"(d[12]),"+f"(d[13]),"+f"(d[14]),"+f"(d[15]),"+f"(d[16]),"+f"(d[17]),"+f"(d[18]),"+f"(d[19]),"+f"(d[20]),"+f"(d[21]),"+f"(d[22]),"+f"(d[23]),"+f"(d[24]),"+f"(d[25]),"+f"(d[26]),"+f"(d[27]),"+f"(d[28]),"+f"(d[29]),"+f"(d[30]),"+f"(d[31]),"+f"(d[32]),"+f"(d[33]),"+f"(d[34]),"+f"(d[35]),"+f"(d[36]),"+f"(d[37]),"+f"(d[38]),"+f"(d[39]),"+f"(d[40]),"+f"(d[41]),"+f"(d[42]),"+f"(d[43]),"+f"(d[44]),"+f"(d[45]),"+f"(d[46]),"+f"(d[47]),"+f"(d[48]),"+f"(d[49]),"+f"(d[50]),"+f"(d[51]),"+f"(d[52]),"+f"(d[53]),"+f"(d[54]),"+f"(d[55]),"+f"(d[56]),"+f"(d[57]),"+f"(d[58]),"+f"(d[59]),"+f"(d[60]),"+f"(d[61]),"+f"(d[62]),"+f"(d[63]),"+f"(d[64]),"+f"(d[65]),"+f"(d[66]),"+f"(d[67]),"+f"(d[68]),"+f"(d[69]),"+f"(d[70]),"+f"(d[71]),"+f"(d[72]),"+f"(d[73]),"+f"(d[74]),"+f"(d[75]),"+f"(d[76]),"+f"(d[77]),"+f"(d[78]),"+f"(d[79]),"+f"(d[80]),"+f"(d[81]),"+f"(d[82]),"+f"(d[83]),"+f"(d[84]),"+f"(d[85]),"+f"(d[86]),"+f"(d[87])
    : "r"(a[0]), "r"(a[1]), "r"(a[2]), "r"(a[3]), "l"(db)); } };
template<> struct WRS<192> { static __device__ __forceinline__ void mma(float* d, const uint32_t* a, uint64_t db) {
  asm volatile("wgmma.mma_async.sync.aligned.m64n192k16.f32.bf16.bf16 {%0,%1,%2,%3,%4,%5,%6,%7,%8,%9,%10,%11,%12,%13,%14,%15,%16,%17,%18,%19,%20,%21,%22,%23,%24,%25,%26,%27,%28,%29,%30,%31,%32,%33,%34,%35,%36,%37,%38,%39,%40,%41,%42,%43,%44,%45,%46,%47,%48,%49,%50,%51,%52,%53,%54,%55,%56,%57,%58,%59,%60,%61,%62,%63,%64,%65,%66,%67,%68,%69,%70,%71,%72,%73,%74,%75,%76,%77,%78,%79,%80,%81,%82,%83,%84,%85,%86,%87,%88,%89,%90,%91,%92,%93,%94,%95}, {%96,%97,%98,%99}, %100, 1, 1, 1, 0;"
    : "+f"(d[0]),"+f"(d[1]),"+f"(d[2]),"+f"(d[3]),"+f"(d[4]),"+f"(d[5]),"+f"(d[6]),"+f"(d[7]),"+f"(d[8]),"+f"(d[9]),"+f"(d[10]),"+f"(d[11]),"+f"(d[12]),"+f"(d[13]),"+f"(d[14]),"+f"(d[15]),"+f"(d[16]),"+f"(d[17]),"+f"(d[18]),"+f"(d[19]),"+f"(d[20]),"+f"(d[21]),"+f"(d[22]),"+f"(d[23]),"+f"(d[24]),"+f"(d[25]),"+f"(d[26]),"+f"(d[27]),"+f"(d[28]),"+f"(d[29]),"+f"(d[30]),"+f"(d[31]),"+f"(d[32]),"+f"(d[33]),"+f"(d[34]),"+f"(d[35]),"+f"(d[36]),"+f"(d[37]),"+f"(d[38]),"+f"(d[39]),"+f"(d[40]),"+f"(d[41]),"+f"(d[42]),"+f"(d[43]),"+f"(d[44]),"+f"(d[45]),"+f"(d[46]),"+f"(d[47]),"+f"(d[48]),"+f"(d[49]),"+f"(d[50]),"+f"(d[51]),"+f"(d[52]),"+f"(d[53]),"+f"(d[54]),"+f"(d[55]),"+f"(d[56]),"+f"(d[57]),"+f"(d[58]),"+f"(d[59]),"+f"(d[60]),"+f"(d[61]),"+f"(d[62]),"+f"(d[63]),"+f"(d[64]),"+f"(d[65]),"+f"(d[66]),"+f"(d[67]),"+f"(d[68]),"+f"(d[69]),"+f"(d[70]),"+f"(d[71]),"+f"(d[72]),"+f"(d[73]),"+f"(d[74]),"+f"(d[75]),"+f"(d[76]),"+f"(d[77]),"+f"(d[78]),"+f"(d[79]),"+f"(d[80]),"+f"(d[81]),"+f"(d[82]),"+f"(d[83]),"+f"(d[84]),"+f"(d[85]),"+f"(d[86]),"+f"(d[87]),"+f"(d[88]),"+f"(d[89]),"+f"(d[90]),"+f"(d[91]),"+f"(d[92]),"+f"(d[93]),"+f"(d[94]),"+f"(d[95])
    : "r"(a[0]), "r"(a[1]), "r"(a[2]), "r"(a[3]), "l"(db)); } };
__device__ __forceinline__ void wg32_tt(float* d, uint64_t da, uint64_t db, int acc) {
  asm volatile("{\n.reg .pred p;\nsetp.ne.b32 p, %18, 0;\nwgmma.mma_async.sync.aligned.m64n32k16.f32.bf16.bf16 {%0,%1,%2,%3,%4,%5,%6,%7,%8,%9,%10,%11,%12,%13,%14,%15}, %16, %17, p, 1, 1, 1, 1;\n}"
    : "+f"(d[0]),"+f"(d[1]),"+f"(d[2]),"+f"(d[3]),"+f"(d[4]),"+f"(d[5]),"+f"(d[6]),"+f"(d[7]),"+f"(d[8]),"+f"(d[9]),"+f"(d[10]),"+f"(d[11]),"+f"(d[12]),"+f"(d[13]),"+f"(d[14]),"+f"(d[15])
    : "l"(da), "l"(db), "r"(acc)); }
__device__ __forceinline__ void wg192_tt(float* d, uint64_t da, uint64_t db, int acc) {
  asm volatile("{\n.reg .pred p;\nsetp.ne.b32 p, %98, 0;\nwgmma.mma_async.sync.aligned.m64n192k16.f32.bf16.bf16 {%0,%1,%2,%3,%4,%5,%6,%7,%8,%9,%10,%11,%12,%13,%14,%15,%16,%17,%18,%19,%20,%21,%22,%23,%24,%25,%26,%27,%28,%29,%30,%31,%32,%33,%34,%35,%36,%37,%38,%39,%40,%41,%42,%43,%44,%45,%46,%47,%48,%49,%50,%51,%52,%53,%54,%55,%56,%57,%58,%59,%60,%61,%62,%63,%64,%65,%66,%67,%68,%69,%70,%71,%72,%73,%74,%75,%76,%77,%78,%79,%80,%81,%82,%83,%84,%85,%86,%87,%88,%89,%90,%91,%92,%93,%94,%95}, %96, %97, p, 1, 1, 1, 1;\n}"
    : "+f"(d[0]),"+f"(d[1]),"+f"(d[2]),"+f"(d[3]),"+f"(d[4]),"+f"(d[5]),"+f"(d[6]),"+f"(d[7]),"+f"(d[8]),"+f"(d[9]),"+f"(d[10]),"+f"(d[11]),"+f"(d[12]),"+f"(d[13]),"+f"(d[14]),"+f"(d[15]),"+f"(d[16]),"+f"(d[17]),"+f"(d[18]),"+f"(d[19]),"+f"(d[20]),"+f"(d[21]),"+f"(d[22]),"+f"(d[23]),"+f"(d[24]),"+f"(d[25]),"+f"(d[26]),"+f"(d[27]),"+f"(d[28]),"+f"(d[29]),"+f"(d[30]),"+f"(d[31]),"+f"(d[32]),"+f"(d[33]),"+f"(d[34]),"+f"(d[35]),"+f"(d[36]),"+f"(d[37]),"+f"(d[38]),"+f"(d[39]),"+f"(d[40]),"+f"(d[41]),"+f"(d[42]),"+f"(d[43]),"+f"(d[44]),"+f"(d[45]),"+f"(d[46]),"+f"(d[47]),"+f"(d[48]),"+f"(d[49]),"+f"(d[50]),"+f"(d[51]),"+f"(d[52]),"+f"(d[53]),"+f"(d[54]),"+f"(d[55]),"+f"(d[56]),"+f"(d[57]),"+f"(d[58]),"+f"(d[59]),"+f"(d[60]),"+f"(d[61]),"+f"(d[62]),"+f"(d[63]),"+f"(d[64]),"+f"(d[65]),"+f"(d[66]),"+f"(d[67]),"+f"(d[68]),"+f"(d[69]),"+f"(d[70]),"+f"(d[71]),"+f"(d[72]),"+f"(d[73]),"+f"(d[74]),"+f"(d[75]),"+f"(d[76]),"+f"(d[77]),"+f"(d[78]),"+f"(d[79]),"+f"(d[80]),"+f"(d[81]),"+f"(d[82]),"+f"(d[83]),"+f"(d[84]),"+f"(d[85]),"+f"(d[86]),"+f"(d[87]),"+f"(d[88]),"+f"(d[89]),"+f"(d[90]),"+f"(d[91]),"+f"(d[92]),"+f"(d[93]),"+f"(d[94]),"+f"(d[95])
    : "l"(da), "l"(db), "r"(acc)); }
__device__ __forceinline__ void wg128_nt(float* d, uint64_t da, uint64_t db, int acc) {
  asm volatile("{\n.reg .pred p;\nsetp.ne.b32 p, %66, 0;\nwgmma.mma_async.sync.aligned.m64n128k16.f32.bf16.bf16 {%0,%1,%2,%3,%4,%5,%6,%7,%8,%9,%10,%11,%12,%13,%14,%15,%16,%17,%18,%19,%20,%21,%22,%23,%24,%25,%26,%27,%28,%29,%30,%31,%32,%33,%34,%35,%36,%37,%38,%39,%40,%41,%42,%43,%44,%45,%46,%47,%48,%49,%50,%51,%52,%53,%54,%55,%56,%57,%58,%59,%60,%61,%62,%63}, %64, %65, p, 1, 1, 0, 1;\n}"
    : "+f"(d[0]),"+f"(d[1]),"+f"(d[2]),"+f"(d[3]),"+f"(d[4]),"+f"(d[5]),"+f"(d[6]),"+f"(d[7]),"+f"(d[8]),"+f"(d[9]),"+f"(d[10]),"+f"(d[11]),"+f"(d[12]),"+f"(d[13]),"+f"(d[14]),"+f"(d[15]),"+f"(d[16]),"+f"(d[17]),"+f"(d[18]),"+f"(d[19]),"+f"(d[20]),"+f"(d[21]),"+f"(d[22]),"+f"(d[23]),"+f"(d[24]),"+f"(d[25]),"+f"(d[26]),"+f"(d[27]),"+f"(d[28]),"+f"(d[29]),"+f"(d[30]),"+f"(d[31]),"+f"(d[32]),"+f"(d[33]),"+f"(d[34]),"+f"(d[35]),"+f"(d[36]),"+f"(d[37]),"+f"(d[38]),"+f"(d[39]),"+f"(d[40]),"+f"(d[41]),"+f"(d[42]),"+f"(d[43]),"+f"(d[44]),"+f"(d[45]),"+f"(d[46]),"+f"(d[47]),"+f"(d[48]),"+f"(d[49]),"+f"(d[50]),"+f"(d[51]),"+f"(d[52]),"+f"(d[53]),"+f"(d[54]),"+f"(d[55]),"+f"(d[56]),"+f"(d[57]),"+f"(d[58]),"+f"(d[59]),"+f"(d[60]),"+f"(d[61]),"+f"(d[62]),"+f"(d[63])
    : "l"(da), "l"(db), "r"(acc)); }
__device__ __forceinline__ void wg96_nt(float* d, uint64_t da, uint64_t db, int acc) {
  asm volatile("{\n.reg .pred p;\nsetp.ne.b32 p, %50, 0;\nwgmma.mma_async.sync.aligned.m64n96k16.f32.bf16.bf16 {%0,%1,%2,%3,%4,%5,%6,%7,%8,%9,%10,%11,%12,%13,%14,%15,%16,%17,%18,%19,%20,%21,%22,%23,%24,%25,%26,%27,%28,%29,%30,%31,%32,%33,%34,%35,%36,%37,%38,%39,%40,%41,%42,%43,%44,%45,%46,%47}, %48, %49, p, 1, 1, 0, 1;\n}"
    : "+f"(d[0]),"+f"(d[1]),"+f"(d[2]),"+f"(d[3]),"+f"(d[4]),"+f"(d[5]),"+f"(d[6]),"+f"(d[7]),"+f"(d[8]),"+f"(d[9]),"+f"(d[10]),"+f"(d[11]),"+f"(d[12]),"+f"(d[13]),"+f"(d[14]),"+f"(d[15]),"+f"(d[16]),"+f"(d[17]),"+f"(d[18]),"+f"(d[19]),"+f"(d[20]),"+f"(d[21]),"+f"(d[22]),"+f"(d[23]),"+f"(d[24]),"+f"(d[25]),"+f"(d[26]),"+f"(d[27]),"+f"(d[28]),"+f"(d[29]),"+f"(d[30]),"+f"(d[31]),"+f"(d[32]),"+f"(d[33]),"+f"(d[34]),"+f"(d[35]),"+f"(d[36]),"+f"(d[37]),"+f"(d[38]),"+f"(d[39]),"+f"(d[40]),"+f"(d[41]),"+f"(d[42]),"+f"(d[43]),"+f"(d[44]),"+f"(d[45]),"+f"(d[46]),"+f"(d[47])
    : "l"(da), "l"(db), "r"(acc)); }
__device__ __forceinline__ void wg80_nn(float* d, uint64_t da, uint64_t db) {
  asm volatile("wgmma.mma_async.sync.aligned.m64n80k16.f32.bf16.bf16 {%0,%1,%2,%3,%4,%5,%6,%7,%8,%9,%10,%11,%12,%13,%14,%15,%16,%17,%18,%19,%20,%21,%22,%23,%24,%25,%26,%27,%28,%29,%30,%31,%32,%33,%34,%35,%36,%37,%38,%39}, %40, %41, 1, 1, 1, 0, 0;"
    : "+f"(d[0]),"+f"(d[1]),"+f"(d[2]),"+f"(d[3]),"+f"(d[4]),"+f"(d[5]),"+f"(d[6]),"+f"(d[7]),"+f"(d[8]),"+f"(d[9]),"+f"(d[10]),"+f"(d[11]),"+f"(d[12]),"+f"(d[13]),"+f"(d[14]),"+f"(d[15]),"+f"(d[16]),"+f"(d[17]),"+f"(d[18]),"+f"(d[19]),"+f"(d[20]),"+f"(d[21]),"+f"(d[22]),"+f"(d[23]),"+f"(d[24]),"+f"(d[25]),"+f"(d[26]),"+f"(d[27]),"+f"(d[28]),"+f"(d[29]),"+f"(d[30]),"+f"(d[31]),"+f"(d[32]),"+f"(d[33]),"+f"(d[34]),"+f"(d[35]),"+f"(d[36]),"+f"(d[37]),"+f"(d[38]),"+f"(d[39])
    : "l"(da), "l"(db)); }
__device__ __forceinline__ void wg8_tn(float* d, uint64_t da, uint64_t db) {
  asm volatile("wgmma.mma_async.sync.aligned.m64n8k16.f32.bf16.bf16 {%0,%1,%2,%3}, %4, %5, 1, 1, 1, 1, 0;"
    : "+f"(d[0]),"+f"(d[1]),"+f"(d[2]),"+f"(d[3])
    : "l"(da), "l"(db)); }

constexpr int BLK = 40;
constexpr int APP = 256;
constexpr int IMG = 1792;
struct Scratch {
  unsigned cnt[24 * 32];
  uint4 modp[5 * 800];
  uint4 gbp[10 * 32];
  uint4 blk[128 * BLK];
  uint4 v[16 * 112];
  uint4 ic[160];
  uint32_t qst[2048];
  uint4 T[1280 * 256];
  uint4 apT[640 * APP];
  uint4 z2n[4 * 32 * IMG];
  uint4 P[128 * IMG];
  uint4 wo[4 * 17920];
};
__device__ __align__(1024) Scratch g_scr;
enum { C_A = 0, C_B = 5, C_W = 10, C_CLR = 11, C_Q = 12, C_M = 13, C_G = 16   };

constexpr uint32_t SM_R = 81920, SM_SP = 212992, SM_TAIL = 229376, SM_TOTAL = 232448;
constexpr uint32_t KV_V = 4480, SM_QIN = SM_R, SM_QOUT = SM_R + 20480, SM_SHIFT = 123904, SM_QRED = 129024;
constexpr uint32_t SM_VT2 = SM_SP, SM_ST2 = SM_SP + 3584, SM_IC = SM_SP + 5632, SM_LN2 = SM_SP + 8192, SM_VT1 = 28672;
constexpr uint32_t SM_BAR = SM_TAIL, SM_EP = SM_BAR + 1056, SM_MODTAB = SM_EP + 16, SM_DUMMY = SM_MODTAB + 80, SM_SILU = SM_DUMMY + 64, SM_PROF = SM_SILU + 1280;
static_assert(SM_PROF + 512 <= SM_TOTAL, "smem");
__device__ __forceinline__ uint32_t offU(int s) { return SM_R + (3 + s) * 16384; }
__device__ __forceinline__ uint32_t offF(int s) { return offU(s) + 4224; }
__host__ __device__ constexpr uint32_t placeB2(int st) { return ((uint32_t)(0xB490206C50ull >> (8 * st)) & 255) * 1024; }
__host__ __device__ constexpr uint32_t placeA2(int st) { return ((uint32_t)(0x48AC4088D8ull >> (8 * st)) & 255) * 1024; }
__host__ __device__ constexpr uint32_t offB3(int p) { return ((uint32_t)(0x48B400254890256Cull >> (8 * p)) & 255) * 1024; }
__host__ __device__ constexpr uint32_t offA3(int c) { return ((0x906CB400u >> (8 * c)) & 255) * 1024; }
constexpr uint32_t SM_XA = 37888, SM_OUT = 110592;
__device__ __forceinline__ int nstart(int n) { return n < 3 ? 224 * n : 640; }
enum {
  B_KV = 0, B_Q = 5, B_F = 6, B_QS = 11, B_INIT = 12,
  B_SH = 13, B_U = 14, B_EP = 19, B_GATE = 20, B_X1 = 21, B_OWN = 22, B_FULL1 = 24, B_A = 32, B_FULL2 = 37,
  B_CH = 42  , B_FB3 = 48, B_QO = 56, B_AV = 57, B_LN = 23,
  B_EMPTY1 = 62, B_EMPTY2 = 70, B_Z1OK = 75, B_X4FREE = 76, B_SPFREE = 77,
  B_ZFREE1 = 78, B_R012 = 79, B_DONE = 80, B_VT = 81, B_REL3 = 82,
  B_PART = 89  , B_ST2 = 99, B_STG = 100  , B_PST = 102, B_FIN = 103, B_PRD = 104, B_VAL = 107,
  B_FO = 116, B_EPI = 121,
  B_QH = 126, B_MT = 127, B_NIL = 128  , B_CLR = 130, B_WO = 131,
  B_COUNT = 132
};
__host__ __device__ constexpr int barCount(int i) { return i < B_EMPTY1 ? 1 : i <= B_ZFREE1 ? 4 : i == B_R012 ? 3 : i == B_DONE ? 15 : i == B_VT ? 112 : i < B_PART ? 8 : i < B_FO ? 128 : 1; }

struct Params {
  const __nv_bfloat16 *shiftk, *ssmk, *ssmD, *bsp, *c, *wmod;
  Scratch* g;
};

__device__ __forceinline__ void mbar_init(uint32_t a, int c) { asm volatile("mbarrier.init.shared::cta.b64 [%0], %1;" ::"r"(a), "r"(c)); }
template <int I0, int I1>
__device__ __forceinline__ void init_bars(uint32_t sb) {
#pragma unroll
  for (int i = I0; i < I1; i++) mbar_init(sb + SM_BAR + i * 8, barCount(i));
}
__device__ __forceinline__ void mbar_arrive(uint32_t a) { asm volatile("mbarrier.arrive.shared::cta.b64 _, [%0];" ::"r"(a) : "memory"); }
__device__ __forceinline__ void mbar_expect(uint32_t a, int b) { asm volatile("mbarrier.arrive.expect_tx.shared::cta.b64 _, [%0], %1;" ::"r"(a), "r"(b) : "memory"); }
__device__ __forceinline__ void mbar_wait(uint32_t a, int ph) {
  asm volatile("{\n.reg .pred p;\nWL:\nmbarrier.try_wait.parity.shared::cta.b64 p, [%0], %1;\n@!p bra WL;\n}" ::"r"(a), "r"(ph) : "memory");
}
__device__ __forceinline__ void mbar_wait2(uint32_t a, uint32_t b, int pa, int pb) {
  asm volatile("{\n.reg .pred p, q;\nWL:\nmbarrier.try_wait.parity.shared::cta.b64 p, [%0], %2;\nmbarrier.try_wait.parity.shared::cta.b64 q, [%1], %3;\nand.pred p, p, q;\n@!p bra WL;\n}" ::"r"(a), "r"(b), "r"(pa), "r"(pb) : "memory");
}
__device__ __forceinline__ bool mbar_test(uint32_t a, int ph) {
  uint32_t r;
  asm volatile("{\n.reg .pred p;\nmbarrier.test_wait.parity.shared::cta.b64 p, [%1], %2;\nselp.u32 %0, 1, 0, p;\n}" : "=r"(r) : "r"(a), "r"(ph) : "memory");
  return __all_sync(0xffffffffu, r);
}
__device__ __forceinline__ void mbar_wait_b(uint32_t a, int ph) {
  asm volatile("{\n.reg .pred p;\n.reg .u32 c;\nmov.u32 c, 0;\nWL:\nmbarrier.try_wait.parity.shared::cta.b64 p, [%0], %1;\n@p bra WD;\n"
               "add.u32 c, c, 1;\nsetp.lt.u32 p, c, 0x10000;\n@p bra WL;\ntrap;\nWD:\n}" ::"r"(a), "r"(ph) : "memory");
}
__device__ __forceinline__ uint32_t mapa(uint32_t a, uint32_t rank) { uint32_t r; asm("mapa.shared::cluster.u32 %0, %1, %2;" : "=r"(r) : "r"(a), "r"(rank)); return r; }
__device__ __forceinline__ void bar_sync(int id, int n) { asm volatile("bar.sync %0, %1;" ::"r"(id), "r"(n) : "memory"); }
__device__ __forceinline__ void bar_arrive(int id, int n) { asm volatile("bar.arrive %0, %1;" ::"r"(id), "r"(n) : "memory"); }
__device__ __forceinline__ unsigned ld_acquire(const void* p) { unsigned v; asm volatile("ld.acquire.gpu.global.u32 %0, [%1];" : "=r"(v) : "l"(p) : "memory"); return v; }
__device__ __forceinline__ unsigned ld_relaxed(const void* p) { unsigned v; asm volatile("ld.relaxed.gpu.global.u32 %0, [%1];" : "=r"(v) : "l"(p) : "memory"); return v; }
__device__ __forceinline__ uint4 ld_relaxed4(const void* p) { uint4 v; asm volatile("ld.relaxed.gpu.global.v4.u32 {%0,%1,%2,%3}, [%4];" : "=r"(v.x), "=r"(v.y), "=r"(v.z), "=r"(v.w) : "l"(p) : "memory"); return v; }
__device__ __forceinline__ void st_relaxed4(void* p, uint4 v) { asm volatile("st.relaxed.gpu.global.v4.u32 [%0], {%1,%2,%3,%4};" ::"l"(p), "r"(v.x), "r"(v.y), "r"(v.z), "r"(v.w) : "memory"); }
__device__ __forceinline__ void st_relaxed(void* p, unsigned v) { asm volatile("st.relaxed.gpu.global.u32 [%0], %1;" ::"l"(p), "r"(v) : "memory"); }
__device__ __forceinline__ void st_relaxed2f(void* p, float a, float b) { asm volatile("st.relaxed.gpu.global.v2.f32 [%0], {%1,%2};" ::"l"(p), "f"(a), "f"(b) : "memory"); }
__device__ __forceinline__ bool valid4(uint4 v) { return max(max(v.x, v.y), max(v.z, v.w)) != 0xffffffffu; }
__device__ __forceinline__ void red_release(unsigned* p) { asm volatile("red.release.gpu.global.add.u32 [%0], 1;" ::"l"(p) : "memory"); }
__device__ __forceinline__ void red_relaxed(unsigned* p) { asm volatile("red.relaxed.gpu.global.add.u32 [%0], 1;" ::"l"(p) : "memory"); }
__device__ __forceinline__ void fence_gpu() { asm volatile("fence.acq_rel.gpu;" ::: "memory"); }
__device__ __forceinline__ void wait_cnt(const Scratch* G, int idx, unsigned target) {
  asm volatile("{\n.reg .pred p;\n.reg .u32 v;\nWL:\nld.acquire.gpu.global.u32 v, [%0];\nsub.s32 v, v, %1;\nsetp.lt.s32 p, v, 0;\n@p bra WL;\n}" ::"l"(G->cnt + idx * 32), "r"(target) : "memory");
}
__device__ __forceinline__ void wait_cnt_b(const Scratch* G, int idx, unsigned target) {
  asm volatile("{\n.reg .pred p;\n.reg .u32 v, c;\nmov.u32 c, 0;\nWL:\nld.acquire.gpu.global.u32 v, [%0];\nsub.s32 v, v, %1;\nsetp.ge.s32 p, v, 0;\n@p bra WD;\n"
               "add.u32 c, c, 1;\nsetp.lt.u32 p, c, 0x80000;\n@p bra WL;\ntrap;\nWD:\n}" ::"l"(G->cnt + idx * 32), "r"(target) : "memory");
}
__device__ __forceinline__ void fence_async_g() { asm volatile("fence.proxy.async.global;" ::: "memory"); }
__device__ __forceinline__ void fence_async_s() { asm volatile("fence.proxy.async.shared::cta;" ::: "memory"); }
#define ELECT "{\n.reg .pred e;\nelect.sync _|e, 0xffffffff;\n@e "
__device__ __forceinline__ void w_expect(uint32_t a, int b) { asm volatile(ELECT "mbarrier.arrive.expect_tx.shared::cta.b64 _, [%0], %1;\n}" ::"r"(a), "r"(b) : "memory"); }
__device__ __forceinline__ void bulk_g2s(uint32_t dst, const void* src, int bytes, uint32_t bar) {
  asm volatile(ELECT "cp.async.bulk.shared::cluster.global.mbarrier::complete_tx::bytes [%0], [%1], %2, [%3];\n}" ::"r"(dst), "l"(src), "r"(bytes), "r"(bar) : "memory");
}
__device__ __forceinline__ void bulk_commit() { asm volatile("cp.async.bulk.commit_group;" ::: "memory"); }
__device__ __forceinline__ void bulk_wait_read0() { asm volatile("cp.async.bulk.wait_group.read 0;" ::: "memory"); }
__device__ __forceinline__ void tma2d(uint32_t dst, const CUtensorMap* m, int c0, int c1, uint32_t bar) {
  asm volatile(ELECT "cp.async.bulk.tensor.2d.shared::cluster.global.mbarrier::complete_tx::bytes [%0], [%1, {%3, %4}], [%2];\n}" ::"r"(dst), "l"(m), "r"(bar), "r"(c0), "r"(c1) : "memory");
}
__device__ __forceinline__ void tma3d(uint32_t dst, const CUtensorMap* m, int c0, int c1, uint32_t bar) {
  asm volatile(ELECT "cp.async.bulk.tensor.3d.shared::cluster.global.mbarrier::complete_tx::bytes [%0], [%1, {%3, %4, %5}], [%2];\n}" ::"r"(dst), "l"(m), "r"(bar), "r"(c0), "r"(c1), "r"(0) : "memory");
}
__device__ __forceinline__ void tma2d_store(const CUtensorMap* m, int c0, int c1, uint32_t src) {
  asm volatile("cp.async.bulk.tensor.2d.global.shared::cta.bulk_group [%0, {%2, %3}], [%1];" ::"l"(m), "r"(src), "r"(c0), "r"(c1) : "memory");
}
__device__ __forceinline__ void tma2d_prefetch(const CUtensorMap* m, int c0, int c1) {
  asm volatile(ELECT "cp.async.bulk.prefetch.tensor.2d.L2.global [%0, {%1, %2}];\n}" ::"l"(m), "r"(c0), "r"(c1) : "memory");
}
__device__ __forceinline__ void tmap_prefetch(const CUtensorMap* m) { asm volatile("prefetch.tensormap [%0];" ::"l"(m) : "memory"); }
__device__ __forceinline__ uint64_t mkdesc(uint32_t addr, uint32_t lbo, uint32_t sbo, uint32_t swz) {
  return (uint64_t)((addr & 0x3FFFF) >> 4) | ((uint64_t)(lbo >> 4) << 16) | ((uint64_t)(sbo >> 4) << 32) | ((uint64_t)swz << 62);
}
#define WG_FENCE() asm volatile("wgmma.fence.sync.aligned;" ::: "memory")
#define WG_COMMIT() asm volatile("wgmma.commit_group.sync.aligned;" ::: "memory")
#define WG_WAIT(n) asm volatile("wgmma.wait_group.sync.aligned " #n ";" ::: "memory")
__device__ __forceinline__ uint32_t lds32(uint32_t a) { uint32_t v; asm volatile("ld.shared.u32 %0, [%1];" : "=r"(v) : "r"(a) : "memory"); return v; }
__device__ __forceinline__ uint32_t lds16(uint32_t a) { uint16_t v; asm volatile("ld.shared.u16 %0, [%1];" : "=h"(v) : "r"(a) : "memory"); return v; }
__device__ __forceinline__ float lds32f(uint32_t a) { float v; asm volatile("ld.shared.f32 %0, [%1];" : "=f"(v) : "r"(a) : "memory"); return v; }
__device__ __forceinline__ uint2 lds64(uint32_t a) { uint2 v; asm volatile("ld.shared.v2.u32 {%0,%1}, [%2];" : "=r"(v.x), "=r"(v.y) : "r"(a) : "memory"); return v; }
__device__ __forceinline__ uint4 lds128(uint32_t a) { uint4 v; asm volatile("ld.shared.v4.u32 {%0,%1,%2,%3}, [%4];" : "=r"(v.x), "=r"(v.y), "=r"(v.z), "=r"(v.w) : "r"(a) : "memory"); return v; }
__device__ __forceinline__ float4 lds128f(uint32_t a) { float4 v; asm volatile("ld.shared.v4.f32 {%0,%1,%2,%3}, [%4];" : "=f"(v.x), "=f"(v.y), "=f"(v.z), "=f"(v.w) : "r"(a) : "memory"); return v; }
__device__ __forceinline__ void sts32(uint32_t a, uint32_t v) { asm volatile("st.shared.u32 [%0], %1;" ::"r"(a), "r"(v) : "memory"); }
__device__ __forceinline__ void sts32f(uint32_t a, float v) { asm volatile("st.shared.f32 [%0], %1;" ::"r"(a), "f"(v) : "memory"); }
__device__ __forceinline__ void sts64(uint32_t a, uint32_t x, uint32_t y) { asm volatile("st.shared.v2.u32 [%0], {%1,%2};" ::"r"(a), "r"(x), "r"(y) : "memory"); }
__device__ __forceinline__ void sts64f(uint32_t a, float x, float y) { asm volatile("st.shared.v2.f32 [%0], {%1,%2};" ::"r"(a), "f"(x), "f"(y) : "memory"); }
__device__ __forceinline__ void sts128(uint32_t a, uint4 v) { asm volatile("st.shared.v4.u32 [%0], {%1,%2,%3,%4};" ::"r"(a), "r"(v.x), "r"(v.y), "r"(v.z), "r"(v.w) : "memory"); }
__device__ __forceinline__ void sts128f(uint32_t a, float x, float y, float z, float w) { asm volatile("st.shared.v4.f32 [%0], {%1,%2,%3,%4};" ::"r"(a), "f"(x), "f"(y), "f"(z), "f"(w) : "memory"); }
__device__ __forceinline__ void stsm4(uint32_t a, uint32_t r0, uint32_t r1, uint32_t r2, uint32_t r3) {
  asm volatile("stmatrix.sync.aligned.m8n8.x4.shared.b16 [%0], {%1,%2,%3,%4};" ::"r"(a), "r"(r0), "r"(r1), "r"(r2), "r"(r3) : "memory");
}
__device__ __forceinline__ void stsm4t(uint32_t a, uint32_t r0, uint32_t r1, uint32_t r2, uint32_t r3) {
  asm volatile("stmatrix.sync.aligned.m8n8.x4.trans.shared.b16 [%0], {%1,%2,%3,%4};" ::"r"(a), "r"(r0), "r"(r1), "r"(r2), "r"(r3) : "memory");
}
__device__ __forceinline__ void ldsm4(uint32_t a, uint32_t& r0, uint32_t& r1, uint32_t& r2, uint32_t& r3) {
  asm volatile("ldmatrix.sync.aligned.m8n8.x4.shared.b16 {%0,%1,%2,%3}, [%4];" : "=r"(r0), "=r"(r1), "=r"(r2), "=r"(r3) : "r"(a) : "memory");
}
__device__ __forceinline__ void ldsm4t(uint32_t a, uint32_t& r0, uint32_t& r1, uint32_t& r2, uint32_t& r3) {
  asm volatile("ldmatrix.sync.aligned.m8n8.x4.trans.shared.b16 {%0,%1,%2,%3}, [%4];" : "=r"(r0), "=r"(r1), "=r"(r2), "=r"(r3) : "r"(a) : "memory");
}
__device__ __forceinline__ void hmma(float* d, uint32_t a0, uint32_t a1, uint32_t a2, uint32_t a3, uint32_t b0, uint32_t b1) {
  asm volatile("mma.sync.aligned.m16n8k16.row.col.f32.bf16.bf16.f32 {%0,%1,%2,%3}, {%4,%5,%6,%7}, {%8,%9}, {%0,%1,%2,%3};"
               : "+f"(d[0]), "+f"(d[1]), "+f"(d[2]), "+f"(d[3]) : "r"(a0), "r"(a1), "r"(a2), "r"(a3), "r"(b0), "r"(b1));
}
__device__ __forceinline__ uint4 ldg128(const void* p) { uint4 v; asm volatile("ld.global.nc.L1::no_allocate.v4.u32 {%0,%1,%2,%3}, [%4];" : "=r"(v.x), "=r"(v.y), "=r"(v.z), "=r"(v.w) : "l"(p)); return v; }
__device__ __forceinline__ uint32_t ldg32(const void* p) { uint32_t v; asm volatile("ld.global.nc.u32 %0, [%1];" : "=r"(v) : "l"(p)); return v; }
__device__ __forceinline__ uint32_t ldg16(const void* p) { uint16_t v; asm volatile("ld.global.nc.u16 %0, [%1];" : "=h"(v) : "l"(p)); return v; }
__device__ __forceinline__ float ldcg32f(const void* p) { float v; asm volatile("ld.global.cg.f32 %0, [%1];" : "=f"(v) : "l"(p) : "memory"); return v; }
__device__ __forceinline__ uint32_t pack2(float lo, float hi) { uint32_t d; asm("cvt.rn.bf16x2.f32 %0, %1, %2;" : "=r"(d) : "f"(hi), "f"(lo)); return d; }
__device__ __forceinline__ float blo(uint32_t x) { return __uint_as_float(x << 16); }
__device__ __forceinline__ float bhi(uint32_t x) { return __uint_as_float(x & 0xffff0000u); }
__device__ __forceinline__ float bround(float x) { return bhi(pack2(0.f, x)); }
__device__ __forceinline__ uint32_t bmul2(uint32_t a, uint32_t b) { uint32_t d; asm("mul.rn.bf16x2 %0, %1, %2;" : "=r"(d) : "r"(a), "r"(b)); return d; }
__device__ __forceinline__ uint32_t badd2(uint32_t a, uint32_t b) { uint32_t d; asm("add.rn.bf16x2 %0, %1, %2;" : "=r"(d) : "r"(a), "r"(b)); return d; }
__device__ __forceinline__ uint32_t bfma2(uint32_t a, uint32_t b, uint32_t c) { uint32_t d; asm("fma.rn.bf16x2 %0, %1, %2, %3;" : "=r"(d) : "r"(a), "r"(b), "r"(c)); return d; }
__device__ __forceinline__ float silu(float x) { return __fdividef(x, 1.f + __expf(-x)); }
__device__ __forceinline__ float gelu2(float a, float k1, float k2) {
  float t;
  asm("tanh.approx.f32 %0, %1;" : "=f"(t) : "f"(a * fmaf(a * a, k2, k1)));
  return fmaf(a, t, a);
}
__device__ __forceinline__ float cb_scale(float cb) { const float c = bround(1.f + cb); return c == 0.f ? 8.6736174e-19f : c; }
__device__ __forceinline__ uint32_t clk32() { uint32_t t; asm volatile("mov.u32 %0, %%clock;" : "=r"(t)::"memory"); return t; }
__device__ __forceinline__ void sleep_until(uint32_t t0) {
#pragma unroll 1
  while (__any_sync(0xffffffffu, (int)(clk32() - t0) < 0)) __nanosleep(20);
}
__device__ __forceinline__ int g2_kb(int i, int m) { return i == 0 ? m : i < 25 ? ((m & 24) + 7 + i) & 31 : (m & 24) + i - 25 + (i - 25 >= (m & 7)); }

#define TSX(mask, id) do {} while (0)
#define TGX(mask, id) do {} while (0)
#define FX(id) do {} while (0)
#define TS1(id) TSX(1, id)
#define TS2(id) TSX(2, id)
#define TS3(id) TSX(4, id)
#define TSS(id) TSX(8, id)

template <int N>
__device__ __forceinline__ void bfly(float* v, int lane, int mask) {
  const bool b = lane & mask;
#pragma unroll
  for (int i = 0; i < N / 2; i++) {
    float mine = b ? v[i + N / 2] : v[i], other = b ? v[i] : v[i + N / 2];
    v[i] = mine + __shfl_xor_sync(0xffffffffu, other, mask);
  }
}
__device__ __forceinline__ float quad_sum(float x) { x += __shfl_xor_sync(0xffffffffu, x, 1); return x + __shfl_xor_sync(0xffffffffu, x, 2); }

template <int T>
__device__ __forceinline__ void conv_step(float* acc, const uint32_t* A, uint64_t db) {
  WG_FENCE();
  if constexpr (T < 4) {
    WRS<192>::mma(acc, A, db + 16 * T);
    WG_FENCE();
    WRS<64 - 16 * T>::mma(acc + 96, A, db + 192 + 16 * T);
  } else {
    WRS<256 - 16 * T>::mma(acc, A, db + 16 * T);
  }
}
__device__ __forceinline__ void conv_loadA(uint32_t* A, uint32_t fa, int T) {
  const uint32_t b = fa + T * 256;
  A[0] = lds32(b); A[2] = lds32(b + 64); A[1] = lds32(b + 128); A[3] = lds32(b + 192);
}
template <int T>
__device__ __forceinline__ void conv_steps(float* acc, uint32_t (*A)[4], uint32_t fa, uint64_t db) {
  conv_step<T>(acc, A[T & 7], db);
  WG_COMMIT();
  if constexpr (T <= 13 && T >= 6) { WG_WAIT(2); conv_loadA(A[(T + 2) & 7], fa, T - 6); }
  if constexpr (T > 0) conv_steps<T - 1>(acc, A, fa, db);
}
template <int N>
__device__ __forceinline__ void zero_acc(float* a) {
#pragma unroll
  for (int i = 0; i < N; i += 2) asm volatile("mov.b64 {%0, %1}, 0;" : "=f"(a[i]), "=f"(a[i + 1]));
}
__device__ __forceinline__ uint32_t ext_frag(float mu, float sg, int q) {
  const float mh = bround(-mu), sh = bround(sg);
  const float lo = q == 0 ? mh : q == 1 ? -mu - mh : sh, hi = q == 0 ? mh : q == 1 ? sh : sg - sh;
  return pack2(lo, hi) & (q == 3 ? 0u : ~0u);
}
__device__ __forceinline__ void hint_cnt(const Scratch* G, int idx, unsigned target) {
  asm volatile("{\n.reg .pred p;\n.reg .u32 v;\nWL:\nld.relaxed.gpu.global.u32 v, [%0];\nsub.s32 v, v, %1;\nsetp.lt.s32 p, v, 0;\n@p bra WL;\n}" ::"l"(G->cnt + idx * 32), "r"(target) : "memory");
}
__device__ __forceinline__ uint32_t opaque(uint32_t x) { asm volatile("" : "+r"(x)); return __shfl_sync(0xffffffffu, x, 0); }
__device__ __forceinline__ uint32_t tagw(uint32_t x, uint32_t par) { return (x & ~1u) | par; }
__device__ __forceinline__ bool fresh4(uint4 a, uint32_t par) { return !((((a.x ^ par) | (a.y ^ par)) | ((a.z ^ par) | (a.w ^ par))) & 1); }
__device__ __forceinline__ uint4 ld_fresh(const uint4* p, uint4 x, uint32_t par) {
#pragma unroll 1
  while ((x.x ^ par) & 1) x = ld_relaxed4(p);
  return x;
}

__global__ void __launch_bounds__(512, 1)
fused_kernel(const __grid_constant__ Params p, const __grid_constant__ CUtensorMap tm_k, const __grid_constant__ CUtensorMap tm_v,
             const __grid_constant__ CUtensorMap tm_q, const __grid_constant__ CUtensorMap tm_wm, const __grid_constant__ CUtensorMap tm_ap,
             const __grid_constant__ CUtensorMap tm_x1, const __grid_constant__ CUtensorMap tm_w4, const __grid_constant__ CUtensorMap tm_wsp,
             const __grid_constant__ CUtensorMap tm_out, const __grid_constant__ CUtensorMap tm_wo) {
  extern __shared__ __align__(1024) unsigned char smem_raw[];
  const uint32_t tstart = clk32();
  const uint32_t sb = __shfl_sync(0xffffffffu, (uint32_t)__cvta_generic_to_shared(smem_raw), 0);
  const int tid = threadIdx.x, lane = tid & 31;
  const int warp = __shfl_sync(0xffffffffu, tid >> 5, 0);
  const int wg = warp >> 2, w = warp & 3, t128 = tid & 127;
  const int r = lane >> 2, q = lane & 3, mi = lane >> 3, rr = lane & 7;
  Scratch* const G = p.g;
  auto BAR = [&](int i) { return sb + SM_BAR + i * 8; };
  unsigned epoch = 0;
  int bid = blockIdx.x;
  unsigned crank, mytpc;
  {
    unsigned smid, nsm;
    asm("mov.u32 %0, %%smid;" : "=r"(smid));
    asm("mov.u32 %0, %%nsmid;" : "=r"(nsm));
    asm("mov.u32 %0, %%cluster_ctarank;" : "=r"(crank));
    mytpc = nsm == 132 ? smid >> 1 : 0;
    if (nsm == 132) {
      const int t = smid >> 1;
      if (t < 32) bid = (t & 7) * 16 + ((t >> 3) << 1);
      else if (t < 60) bid = ((t - 32) % 7 + 1) * 16 + 8 + (((t - 32) / 7) << 1);
      else bid = t < 62 ? 2 * t + 8 : 2 * t - 116;
      bid += crank;
    }
  }
  if (warp == 13) epoch = ld_relaxed(G->cnt + (lane == 14 && bid < 128 && ALIGN2 && STOP_AFTER >= 3 ? C_G + (bid >> 4) : min(lane, 13)) * 32);
  const uint4 ones = make_uint4(~0u, ~0u, ~0u, ~0u);
  if (bid >= 128) {
    const int j = bid - 128, nit = j < 2 ? 3 : 2;
    constexpr uint32_t S_TAB = SM_SP, S_SILU = SM_SP + 4096, S_FULL = SM_TAIL, S_EMPTY = S_FULL + 96;
    if (tid < 448) st_relaxed4(G->v + ((tid / 112) * 4 + j) * 112 + tid % 112, ones);
    if (tid < nit * 32) st_relaxed4(G->gbp + ((tid >> 5) * 4 + j) * 32 + lane, ones);
    if (lane == 0 && warp >= 8 && warp < 10) {
#pragma unroll
      for (int i = 0; i < 12; i++) mbar_init(sb + S_FULL + (warp - 8) * 96 + i * 8, warp == 9 ? 4 : 1);
    }
    asm volatile("fence.mbarrier_init.release.cluster;" ::: "memory");
    if (tid < 320) { const uint32_t c = ldg32(p.c + tid * 2); sts32(sb + S_SILU + tid * 4, pack2(silu(blo(c)), silu(bhi(c)))); }
    fence_async_s();
    if (warp == 13) sts32(sb + SM_EP, __reduce_min_sync(0xffffffffu, epoch / (lane == 10 ? 4u : lane == 11 ? 132u : 128u) + 1u));
    __syncthreads();
    if (warp < 8) {
      int st = wg, ph = 0, u = wg;
      auto next = [&]() { if (lane == 0) mbar_arrive(sb + S_EMPTY + st * 8); u += 2; st += 2; if (st >= 12) { st -= 12; ph ^= 1; } };
      const uint64_t dA = mkdesc(sb, 0, 1024, 1);
      const uint32_t par = lds32(sb + SM_EP) & 1;
      sleep_until(tstart + 6000);
      wait_cnt_b(G, C_M, lds32(sb + SM_EP) * 128u);
#pragma unroll 1
      for (int i = warp; i < 10; i += 8) {
        const int vec = i >= 5, s = i - 5 * vec;
        uint4 x[5];
        int spin = 0;
        bool ok;
#pragma unroll 1
        do {
          ok = true;
#pragma unroll
          for (int k = 0; k < 5; k++) x[k] = ld_relaxed4(G->modp + k * 800 + (s * 5 + 3 + vec) * 32 + lane);
#pragma unroll
          for (int k = 0; k < 5; k++) ok &= fresh4(x[k], par);
          if (++spin > (1 << 19)) __trap();
        } while (!__all_sync(0xffffffffu, ok));
#define SUM5(f) bround((__uint_as_float(x[0].f) + __uint_as_float(x[4].f) + __uint_as_float(x[2].f)) + (__uint_as_float(x[1].f) + __uint_as_float(x[3].f)))
        float a = SUM5(x), b = SUM5(y), c = SUM5(z), d = SUM5(w);
        if (!vec) { a = cb_scale(a); b = cb_scale(b); c = cb_scale(c); d = cb_scale(d); }
        sts64(sb + S_TAB + (s * 16 + (lane >> 1)) * 32 + vec * 16 + (lane & 1) * 8, pack2(a, b), pack2(c, d));
      }
      fence_async_s();
      bar_sync(1, 256);
      TSS(warp == 0 ? 10 : 127);
#pragma unroll 1
      for (int part = 0; part < 2; part++) {
        float d[32];
        zero_acc<32>(d);
#pragma unroll 1
        while (u < part * 20 + 20) {
          const uint64_t da = dA + st * 1024, db = mkdesc(sb + S_TAB + (u - part * 20) * 128, 32, 128, 0);
          mbar_wait(sb + S_FULL + st * 8, ph);
          WG_FENCE();
#pragma unroll
          for (int i = 0; i < 8; i++) wg8_tn(d + i * 4, da + (i & 3) * 256 + (i >> 2) * 128, db + (i >> 2) * 4);
          WG_COMMIT();
          WG_WAIT(0);
          next();
        }
        const int c0 = w * 16 + r - (((part ? 0 : 864) + nstart(j)) & 63);
        float2* dst = (float2*)G->v + ((wg * 2 + part) * 4 + j) * 224 + c0;
#pragma unroll
        for (int i = 0; i < 8; i++) if (q == 0 && (unsigned)(c0 + (i >> 1) * 64 + (i & 1) * 8) < 224u) st_relaxed2f(dst + (i >> 1) * 64 + (i & 1) * 8, d[2 * i] + d[2 * i + 16], d[2 * i + 1] + d[2 * i + 17]);
        TSS(warp == 0 ? 1 + part : 127);
      }
#pragma unroll 1
      for (int k = 0; k < nit; k++) {
        float d[32];
        zero_acc<32>(d);
#pragma unroll 1
        while (u < 45 + k * 5) {
          const uint64_t da = dA + st * 1024, db = mkdesc(sb + S_SILU + (u - 40 - k * 5) * 256, 16, 128, 0);
          mbar_wait(sb + S_FULL + st * 8, ph);
          WG_FENCE();
#pragma unroll
          for (int i = 0; i < 8; i++) wg8_tn(d + i * 4, da + i * 128, db + i * 2);
          WG_COMMIT();
          WG_WAIT(0);
          next();
        }
        float* dst = (float*)(G->gbp + (k * 4 + j) * 32) + wg * 64 + w * 16 + r;
        if (q == 0) {
          st_relaxed(dst, __float_as_uint(((d[0] + d[4]) + (d[8] + d[12])) + ((d[16] + d[20]) + (d[24] + d[28]))));
          st_relaxed(dst + 8, __float_as_uint(((d[2] + d[6]) + (d[10] + d[14])) + ((d[18] + d[22]) + (d[26] + d[30]))));
        }
        TSS(warp == 0 ? 20 + k : 127);
      }
#pragma unroll 1
      while (u < 61 + nit * 5) {
        const int b = u - 40 - nit * 5, g = (b / 3) * 16 + 4 * w, c = g < 84 ? g / 28 : 3, cc = (b % 3) * 8 - (j & 1) * 4;
        uint32_t* dst = (uint32_t*)(G->wo + j * 17920 + (((c ^ j) < 2 ? c ^ j : 2 + (c & 1)) * 28 + g - (nstart(c) >> 3)) * 160 + cc * 8) + lane;
        mbar_wait(sb + S_FULL + st * 8, ph);
        if (g < 108) {
          uint32_t a[8][4];
#pragma unroll
          for (int i = 0; i < 8; i++) ldsm4t(sb + st * 16384 + ((w * 4 + (i >> 1)) * 8 + rr) * 128 + ((((i & 1) * 4 + mi) ^ rr) << 4), a[i][0], a[i][1], a[i][2], a[i][3]);
#pragma unroll
          for (int i = 0; i < 8; i++) {
            uint32_t* o = dst + (i >> 1) * 640 + (i & 1) * 128;
            if ((unsigned)(cc + (i & 1) * 4) < 20u) { o[0] = a[i][0]; o[32] = a[i][1]; o[64] = a[i][2]; o[96] = a[i][3]; }
          }
        }
        __syncwarp();
        next();
      }
      bar_sync(1, 256);
      if (tid == 0) red_release(G->cnt + C_W * 32);
      TSS(warp == 0 ? 3 : 127);
    } else if (tid == 256) {
      red_release(G->cnt + C_CLR * 32);
    } else if (warp >= 14) {
      if (tid == 480) { tmap_prefetch(&tm_w4); tmap_prefetch(&tm_wm); tmap_prefetch(&tm_wo); }
      sleep_until(tstart + T_SPARE);
      uint32_t fb = sb + S_FULL + (warp - 14) * 8, dst = sb + (warp - 14) * 16384, ph = 1;
      auto slot = [&]() { mbar_wait_b(fb + 96, ph); w_expect(fb, 16384); };
      auto next = [&]() { fb += 16; dst += 32768; if (dst >= sb + 196608) { fb -= 96; dst -= 196608; ph ^= 1; } };
      int x = warp - 14;
#pragma unroll 1
      for (; x < 40; x += 2) { slot(); tma3d(dst, &tm_w4, ((x < 20 ? 864 : 0) + nstart(j)) & ~63, (x < 20 ? x : x - 20) * 32, fb); next(); }
      x -= 40;
#pragma unroll 1
      for (int k = 0; k < nit; k++) {
#pragma unroll 1
        for (; x < 5; x += 2) { slot(); tma2d(dst, &tm_wm, 3200 + (k * 4 + j) * 64, x * 128, fb); next(); }
        x -= 5;
      }
#pragma unroll 1
      for (int k = 0; k < 7; k++) {
#pragma unroll 1
        for (; x < 3; x += 2) { slot(); tma2d(dst, &tm_wo, ((j * 160) & ~63) + x * 64, k * 128, fb); next(); }
        x -= 3;
      }
    }
    return;
  }
  const int m = (bid >> 5) * 8 + ((bid >> 1) & 7), n = ((bid >> 3) & 2) + (bid & 1), tile = m * 4 + n;

  if (warp >= 14) {
    if (tid == 448) { mbar_init(BAR(B_KV), 1); asm volatile("fence.mbarrier_init.release.cluster;" ::: "memory"); }
    bar_sync(8, 64);
    if (warp == 14) w_expect(BAR(B_KV), 8576);
    tma2d(sb + (warp - 14) * KV_V, warp == 14 ? &tm_k : &tm_v, (bid & 1) * 64, (bid >> 1) * 32 - 45 + 3 * warp, BAR(B_KV));
    if (tid == 448) {
      init_bars<1, 13>(sb);
      mbar_expect(BAR(B_QS), 1024); mbar_expect(BAR(B_Q), 20480);
      asm volatile("fence.mbarrier_init.release.cluster;" ::: "memory");
    }
  } else if (lane == 0) {
    if (warp == 13) init_bars<B_FO, B_COUNT>(sb);
    else if (warp >= 6) {
      const uint32_t a = BAR(13 + (12 - warp) * 7);
#pragma unroll
      for (int i = 0; i < 7; i++) mbar_init(a + i * 8, 1);
    } else if (warp >= 3) {
      const uint32_t a = BAR(B_PART + (warp - 3) * 9);
#pragma unroll
      for (int i = 0; i < 9; i++) mbar_init(a + i * 8, 128);
    } else if (warp >= 1) {
      const uint32_t a = BAR(B_EMPTY1 + (warp - 1) * 8);
#pragma unroll
      for (int i = 0; i < 8; i++) mbar_init(a + i * 8, 4);
    } else init_bars<B_ZFREE1, B_PART>(sb);
    asm volatile("fence.mbarrier_init.release.cluster;" ::: "memory");
  }
  __syncwarp();
  if (warp == 12) { w_expect(BAR(B_SH), 5120); bulk_g2s(sb + SM_SHIFT, p.shiftk, 5120, BAR(B_SH)); }
  if (warp == 14) bar_arrive(0, 512); else bar_sync(0, 512);
  if (warp == 13) TGX(15, 124);
  if (tid == 384) asm volatile("st.shared::cluster.u32 [%0], %1;" ::"r"(mapa(sb + SM_EP + 4, crank ^ 1)), "r"(mytpc) : "memory");
  if (warp == 12) asm volatile("barrier.cluster.arrive.release.aligned;" ::: "memory"); else asm volatile("barrier.cluster.arrive.relaxed.aligned;" ::: "memory");

  if (wg < 2) {
    asm volatile("setmaxnreg.inc.sync.aligned.u32 192;");
    const int R0 = m * 64 + w * 16 + r;
    uint32_t par = 0;
    if (bid >= 125) { mbar_wait(BAR(B_EP), 0); par = lds32(sb + SM_EP) & 1; }
    else {
      const int ct = bid / 5, vec = ct % 5, row = (bid % 5) * 128 + (tid >> 4) * 8;
      const __nv_bfloat16* wp = p.wmod + (size_t)row * 3840 + (vec < 3 ? vec : 7 - vec) * 640 + (ct / 5) * 128 + (tid & 15) * 8;
      const uint32_t cv = ldg16(p.c + (row & ~15) + (lane & 15));
      uint4 x[8];
#pragma unroll
      for (int i = 0; i < 8; i++) { if (!(i & 3)) sleep_until(tstart + T_W0 + (i >> 2) * W_GAP); x[i] = ldg128(wp + i * 3840); }
      mbar_wait(BAR(B_EP), 0);
      par = lds32(sb + SM_EP) & 1;
      const float cs = bround(silu(blo(cv)));
      float a[8] = {0.f, 0.f, 0.f, 0.f, 0.f, 0.f, 0.f, 0.f};
#pragma unroll
      for (int i = 0; i < 8; i++) {
        const float c = __shfl_sync(0xffffffffu, cs, (lane >> 4) * 8 + i);
        a[0] = fmaf(c, blo(x[i].x), a[0]); a[1] = fmaf(c, bhi(x[i].x), a[1]); a[2] = fmaf(c, blo(x[i].y), a[2]); a[3] = fmaf(c, bhi(x[i].y), a[3]);
        a[4] = fmaf(c, blo(x[i].z), a[4]); a[5] = fmaf(c, bhi(x[i].z), a[5]); a[6] = fmaf(c, blo(x[i].w), a[6]); a[7] = fmaf(c, bhi(x[i].w), a[7]);
      }
      bfly<8>(a, lane, 16);
      sts128f(sb + SM_SP + warp * 512 + (lane & 15) * 32 + (lane >> 4) * 16, a[0], a[1], a[2], a[3]);
      bar_sync(9, 256);
      if (!wg) {
        float t = 0.f;
#pragma unroll
        for (int i = 0; i < 8; i++) t += lds32f(sb + SM_SP + i * 512 + tid * 4);
        st_relaxed((float*)G->modp + (bid % 5) * 3200 + ct * 128 + tid, tagw(__float_as_uint(t), par));
      }
      TS1(warp == 0 ? 80 : 127);
    }
    if (!wg) { bar_sync(4, 128); if (tid == 0) { red_relaxed(G->cnt + C_M * 32); mbar_arrive(BAR(B_CLR)); } __syncwarp(); }
    {
      const uint32_t lofs = (r & 1) ? (16 + 4 * (4 * w + ((r - 1) >> 1) - q)) : (16 + 4160 + 4 * (4 * w + (r >> 1) - 1 - q));
      uint32_t A[8][4];
      bool late = false;
#pragma unroll 1
      for (int s = -1 - wg; s < 5; s += 2) {
        float acc[128];
        zero_acc<128>(acc);
        if (LATEFO && late) {
          mbar_wait(BAR(B_FO + s), 0);
#pragma unroll
          for (int i = 15; i >= 8; i--) conv_loadA(A[i & 7], sb + offF(s) + lofs, i);
          late = false;
        }
        if (s >= 0) {
          if (s == 2) TS1(w == 0 ? 88 : 127);
          mbar_wait(BAR(B_U + s), 0);
          const uint32_t ua = sb + offU(s) + t128 * 16;
          if (((lds32(ua) ^ par) | (lds32(ua + 2048) ^ par)) & 1) {
            FX(118);
            const uint4* up = G->T + (s * 128 + bid) * 256 + t128;
            sts128(ua, ld_fresh(up, lds128(ua), par)); sts128(ua + 2048, ld_fresh(up + 128, lds128(ua + 2048), par));
            fence_async_s();
          }
          bar_sync(4 + wg, 128);
          if (CONV_MUTEX && s) bar_sync(10 + wg, 256);
          TS1(w == 0 ? 10 + s : 127);
          conv_steps<15>(acc, A, sb + offF(s) + lofs, mkdesc(sb + offU(s), 64, 128, 0));
          if (s == 4) bar_arrive(6, 256); else if (CONV_MUTEX) bar_arrive(11 - wg, 256);
          WG_WAIT(0);
          if (s == 2) TS1(w == 0 ? 34 : 127);
        }
        if (s < 3) {
          if (LATEFO && s >= 0 && !mbar_test(BAR(B_FO + s + 2), 0)) late = true;
          else mbar_wait(BAR(B_FO + s + 2), 0);
#pragma unroll
          for (int i = 15; i >= 8; i--) conv_loadA(A[i & 7], sb + offF(s + 2) + lofs, i);
        }
        if (s < 0) continue;
        const uint32_t pa = sb + s * 16384 + w * 4096 + (255 + w - lane) * 16;
        if (lane < w) sts128(sb + s * 16384 + w * 4096 + lane * 16, make_uint4(0, 0, 0, 0));
#pragma unroll
        for (int x = 0; x < 8; x++) {
          uint32_t pk[4];
#pragma unroll
          for (int i = 0; i < 4; i++) {
            const int jj = 4 * x + i;
            float lo = acc[4 * jj], hi = acc[4 * jj + 1];
            if (jj < 31) { lo += acc[4 * jj + 6]; hi += acc[4 * jj + 7]; }
            pk[i] = pack2(lo, hi);
          }
          stsm4t(x == 0 && lane < w ? sb + SM_DUMMY + lane * 16 : pa - x * 512, pk[0], pk[1], pk[2], pk[3]);
        }
        mbar_arrive(BAR(B_PART + s));
        TS1(w == 0 ? 15 + s : 127);
      }
    }
    if (STOP_AFTER >= 2) {
      float z[112];
#pragma unroll
      for (int i = 0; i < 112; i++) asm volatile("" : "=f"(z[i]));
      uint32_t zb[56];
      const uint32_t bsr0 = ldg16(p.bsp + R0) * 0x10001u, bsr1 = ldg16(p.bsp + R0 + 8) * 0x10001u;
      const uint32_t za = sb + (mi >> 1) * 1024 + (16 * w + (mi & 1) * 8 + rr) * 16;
      const uint32_t tg0 = !wg && (lane & 7) == 2 * w, tg1 = !wg && (lane & 7) == 2 * w + 1;
      const bool shifted = !wg ^ (n == 1);
      {
        if (wg) {
          float red[16];
#pragma unroll
          for (int i = 0; i < 16; i++) red[i] = 0.f;
          const int ch = w * 8 + (lane >> 3) + (lane & 4);
          const uint32_t xa = sb + ch * 128 + (((crank * 4 + q) ^ (ch & 7)) << 4), ia = sb + SM_IC + ch * 4;
          asm volatile("barrier.cluster.wait.aligned;" ::: "memory");
#pragma unroll 1
          for (int s = 0; s < 5; s++) {
            uint32_t su[4], sq[4];
            mbar_wait(BAR(B_AV + s), 0);
#pragma unroll
            for (int i = 0; i < 4; i++) {
              const uint4 x = lds128(xa + s * 16384 + i * 4096);
              const float icf = lds32f(ia + s * 512 + i * 128);
              const uint32_t ic = pack2(icf, icf), xv[4] = {x.x, x.y, x.z, x.w};
#pragma unroll
              for (int j = 0; j < 4; j++) {
                const uint32_t u = bmul2(xv[j], ic);
                su[j] = i ? badd2(su[j], u) : u; sq[j] = i ? bfma2(u, u, sq[j]) : bmul2(u, u);
              }
            }
#pragma unroll
            for (int j = 0; j < 4; j++) { red[2 * j] += blo(su[j]); red[2 * j + 1] += bhi(su[j]); red[8 + 2 * j] += blo(sq[j]); red[9 + 2 * j] += bhi(sq[j]); }
          }
          bfly<16>(red, lane, 16); bfly<8>(red, lane, 8); bfly<4>(red, lane, 4);
          const uint32_t da = sb + SM_ST2 + w * 512 + (lane >> 4) * 256 + (crank * 32 + q * 8 + (lane & 8) / 2 + (lane & 4) / 2) * 4;
#pragma unroll
          for (int i = 0; i < 2; i++)
            asm volatile("st.async.weak.shared::cluster.mbarrier::complete_tx::bytes.v2.f32 [%0], {%1, %2}, [%3];" ::"r"(mapa(da, i)), "f"(red[0]), "f"(red[1]), "r"(mapa(BAR(B_LN), i)) : "memory");
          TS2(w == 0 ? 67 : 127);
        }
        uint4 l0 = make_uint4(0, 0, 0, 0);
        float4 l1 = make_float4(0.f, 0.f, 0.f, 0.f);
        {
          const uint64_t dB1 = mkdesc(sb + SM_R, 4096, 1024, 1);
          uint64_t da = mkdesc(sb, 0, 1024, 1);
          bar_sync(6 + wg, 256);
#pragma unroll 1
          for (int s = wg * 5; s < wg * 5 + 5; s++) {
            const uint32_t fb = BAR(B_FULL1) + (s & 1) * 32, ph = (s >> 1) & 1;
            const uint64_t dx = dB1 + (s & 1) * 4096 + (shifted ? 256 : 0), dy = dB1 + (s & 1) * 4096 + (shifted ? 4 : 768);
            const uint32_t e0 = s == wg * 5 ? BAR(B_NIL) : BAR(B_EMPTY1 + 6) - (s & 1) * 32, e1 = BAR(B_EMPTY1) + (s & 1) * 32;
            const uint32_t x0 = BAR(s == 7 ? B_Z1OK : s == 9 ? B_EMPTY2 + 1 : B_NIL), x1 = BAR(s >= 8 ? B_EMPTY2 + 2 * (s - 8) : B_NIL);
            if (!wg) { mbar_wait(BAR(B_AV + s), 0); TS2(w == 0 ? 20 + s : 127); }
            if (s == 6) { l0 = lds128(sb + SM_LN2 + t128 * 16); l1 = lds128f(sb + SM_LN2 + 2048 + t128 * 16); }
#pragma unroll
            for (int j = 0; j < 2; j++) {
              mbar_wait2(fb + j * 16, fb + j * 16 + 8, ph, ph);
              WG_FENCE();
#pragma unroll
              for (int i = 0; i < 4; i++) wg32_tt(z + 96, da + j * 512 + i * 128, dy + j * 2048 + (i >> 1) * 1024 + (i & 1) * 128, i || j || s != wg * 5);
#pragma unroll
              for (int i = 0; i < 4; i++) wg192_tt(z, da + j * 512 + i * 128, dx + j * 2048 + (i >> 1) * 1024 + (i & 1) * 128, i || j || s != wg * 5);
              WG_COMMIT();
              WG_WAIT(1);
              if (lane == 0) { mbar_arrive(j ? e1 : e0); mbar_arrive((j ? e1 : e0) + 8); mbar_arrive(j ? x1 : x0); }
            }
            da += 1024;
          }
        }
        TS2(warp == 0 ? 25 : 127);
        if (wg) {
          WG_WAIT(0);
          if (lane == 0) { mbar_arrive(BAR(B_EMPTY2 + 3)); mbar_arrive(BAR(B_EMPTY2 + 4)); }
          TS2(w == 0 ? 32 : 127);
        } else {
          mbar_wait(BAR(B_ST2), 0);
          l0 = lds128(sb + SM_LN2 + t128 * 16); l1 = lds128f(sb + SM_LN2 + 2048 + t128 * 16);
        }
        const float k10 = __uint_as_float(l0.z), k11 = __uint_as_float(l0.w), k20 = l1.x, k21 = l1.y, sg0 = l1.z, sg1 = l1.w;
        const uint32_t ext[4] = {l0.x, l0.y, 0u, 0u};
        mbar_wait(BAR(B_VT), wg);
        TS2(warp == 0 ? 26 : 127);
        const uint64_t dv = mkdesc(sb + (wg ? SM_VT1 : SM_VT2), 0, 128, 0);
        WG_FENCE();
        WRS<192>::mma(z, ext, dv + (shifted ? 32 : 0)); WRS<32>::mma(z + 96, ext, dv + (shifted ? 0 : 192));
        WG_COMMIT();
        if (!wg && GATE7 < 0) bar_arrive(7, 256);
        WG_WAIT(0);
        if (!wg && lane == 0) { mbar_arrive(BAR(B_EMPTY1 + 2)); mbar_arrive(BAR(B_EMPTY1 + 3)); mbar_arrive(BAR(B_SPFREE)); }
        TS2(w == 0 ? 27 + 6 * wg : 127);
        float s0 = 0.f, q0 = 0.f, s1 = 0.f, q1 = 0.f;
        uint32_t keep = n == 3 ? 0u : ~0u;
        asm volatile("" : "+r"(keep));
#pragma unroll
        for (int g = 0; g < 7; g++) {
          uint32_t su0, sq0, su1, sq1;
#pragma unroll
          for (int i = 0; i < 4; i++) {
            const int j = (4 * g + 24 + i) % 28;
            const uint32_t a = pack2(gelu2(z[4 * j], k10, k20), gelu2(z[4 * j + 1], k10, k20)), b = pack2(gelu2(z[4 * j + 2], k11, k21), gelu2(z[4 * j + 3], k11, k21));
            zb[2 * j] = a; zb[2 * j + 1] = b;
            su0 = i ? badd2(su0, a) : a; sq0 = i ? bfma2(a, a, sq0) : bmul2(a, a);
            su1 = i ? badd2(su1, b) : b; sq1 = i ? bfma2(b, b, sq1) : bmul2(b, b);
          }
          if (g == GATE7 && !wg) bar_arrive(7, 256);
          if (g == 0) { su0 &= keep; sq0 &= keep; su1 &= keep; sq1 &= keep; }
          s0 += blo(su0) + bhi(su0); q0 += blo(sq0) + bhi(sq0); s1 += blo(su1) + bhi(su1); q1 += blo(sq1) + bhi(sq1);
        }
        s0 = quad_sum(s0); q0 = quad_sum(q0); s1 = quad_sum(s1); q1 = quad_sum(q1);
        float c0 = k10 * (0.5f / 0.7978845608028f), c1 = k11 * (0.5f / 0.7978845608028f), e0 = 0.f, e1 = 0.f;
        if (!wg) {
          if (q == 0) st_relaxed4(G->blk + tile * BLK + w * 8 + r, make_uint4(__float_as_uint(s0), __float_as_uint(q0), __float_as_uint(s1), __float_as_uint(q1)));
          TS2(w == 0 ? 28 : 127);
          const uint4* zq = G->blk + (m * 4 + q) * BLK + w * 8 + r;
          uint4 x;
#pragma unroll 1
          do x = ld_relaxed4(zq); while (!__all_sync(0xffffffffu, valid4(x)));
          TS2(w == 0 ? 29 : 127);
          s0 = quad_sum(__uint_as_float(x.x)) * (1.f / 864.f); q0 = quad_sum(__uint_as_float(x.y)); s1 = quad_sum(__uint_as_float(x.z)) * (1.f / 864.f); q1 = quad_sum(__uint_as_float(x.w));
          c0 = rsqrtf(fmaf(4e-5f * sg0, sg0, fmaxf(q0 * (1.f / 864.f) - s0 * s0, 0.f))); c1 = rsqrtf(fmaf(4e-5f * sg1, sg1, fmaxf(q1 * (1.f / 864.f) - s1 * s1, 0.f)));
          e0 = -s0 * c0; e1 = -s1 * c1;
        }
        {
          const uint32_t cp0 = pack2(c0, c0), ep0 = pack2(e0, e0), cp1 = pack2(c1, c1), ep1 = pack2(e1, e1);
#pragma unroll
          for (int j = 0; j < 28; j++) { zb[2 * j] = (bfma2(zb[2 * j], cp0, ep0) & ~tg0) | (par & tg0); zb[2 * j + 1] = (bfma2(zb[2 * j + 1], cp1, ep1) & ~tg1) | (par & tg1); }
        }
        if (!wg) {
          uint32_t* px = (uint32_t*)(G->z2n + (n * 32 + m) * IMG + (shifted ? 256 : 0) + w * 16) + lane;
          uint32_t* py = px - (shifted ? 7168 : 0);
#pragma unroll
          for (int j = 0; j < 56; j++) (j < 48 ? px : py)[(j >> 1) * 256 + (j & 1) * 32] = zb[j];
          bar_sync(4, 128);
          if (t128 < 2) st_relaxed4(G->blk + tile * BLK + 32 + t128, make_uint4(1u, 1u, 1u, 1u));
          TS2(w == 0 ? 36 : 127);
        }
        if (STOP_AFTER >= 3 || !wg) {
          mbar_wait(BAR(wg ? B_ZFREE1 : B_Z1OK), 0);
          uint32_t zx = za + (shifted ? 4096 : 0), zy = za - (shifted ? 24576 : 0);
          asm volatile("" : "+r"(zx), "+r"(zy));
#pragma unroll
          for (int j = 0; j < 28; j += 2) stsm4((j < 24 ? zx : zy) + j * 1024, zb[2 * j], zb[2 * j + 1], zb[2 * j + 2], zb[2 * j + 3]);
          fence_async_s();
          mbar_arrive(BAR(B_STG + wg));
        }
        TS2(w == 0 ? (wg ? 68 : 30) : 127);
      }
      if (STOP_AFTER >= 3) {
        float g[112];
#pragma unroll
        for (int i = 0; i < 112; i++) asm volatile("" : "=f"(g[i]));
        if (!wg) {
          auto step = [&](uint64_t da, uint64_t db, int acc) {
            WG_FENCE();
#pragma unroll
            for (int j = 0; j < 4; j++) wg96_nt(g + 64, da + j * 2, db + j * 16 + 1024, acc || j);
#pragma unroll
            for (int j = 0; j < 4; j++) wg128_nt(g, da + j * 2, db + j * 16, acc || j);
            WG_COMMIT();
          };
          mbar_wait(BAR(B_STG), 0);
          mbar_wait(BAR(B_OWN), 0);
          TS3(w == 0 ? 96 : 127);
          step(mkdesc(sb + SM_SP, 16, 1024, 1), mkdesc(sb, 128, 1024, 0), 0);
#pragma unroll 1
          for (int rnd = 0;; rnd++) {
            const uint32_t sx = opaque(sb);
            const uint64_t dA2 = mkdesc(sx, 16, 1024, 1), dB2 = mkdesc(sx, 128, 1024, 0);
            const uint32_t fb = BAR(rnd ? B_FULL2 : B_VAL), e0 = BAR(rnd ? B_EMPTY2 + 4 : B_ZFREE1);
#pragma unroll
            for (int st = 0; st < 5; st++) {
              mbar_wait(fb + st * 8, rnd & 1);
              if (st == 0 && rnd == WARM_RND) bar_arrive(7, 256);
              if (st == 0) { TS3(w == 0 ? 97 + rnd : 127); TGX(4, w == 0 ? 110 + rnd : 127); }
              step(dA2 + (placeA2(st) >> 4), dB2 + (placeB2(st) >> 4), 1);
              WG_WAIT(1);
              if (lane == 0) mbar_arrive(st ? BAR(B_EMPTY2 + st - 1) : e0);
              if (st == 0 && rnd == 6) goto g2_done;
            }
          }
        g2_done:
          mbar_wait(BAR(B_STG + 1), 0);
#pragma unroll
          for (int j = 0; j < 28; j += 2) ldsm4(za + j * 1024, zb[2 * j], zb[2 * j + 1], zb[2 * j + 2], zb[2 * j + 3]);
          bar_sync(4, 128);
          WG_WAIT(0);
          if (lane == 0) mbar_arrive(BAR(B_EMPTY2));
          TS3(w == 0 ? 38 : 127);
        } else if (WARM_RND >= 0) bar_sync(7, 256);
#pragma unroll
        for (int j = 0; j < 56; j++) zb[j] = (bmul2(zb[j], badd2(pack2(g[2 * j], g[2 * j + 1]), (j & 1) ? bsr1 : bsr0)) & ~((j & 1) ? tg1 : tg0)) | (par & ((j & 1) ? tg1 : tg0));
        {
          const uint32_t pa = wg ? sb + SM_DUMMY : za, ps = wg ? 0 : 1024;
#pragma unroll
          for (int j = 0; j < 28; j += 2) stsm4(pa + j * ps, zb[2 * j], zb[2 * j + 1], zb[2 * j + 2], zb[2 * j + 3]);
          fence_async_s();
          if (!wg) mbar_arrive(BAR(B_PST));
          TS3(warp == 0 ? 40 : 127);
        }
      }
      if (STOP_AFTER >= 4) {
        float o[40];
        zero_acc<40>(o);
#pragma unroll 1
        for (int it = wg ^ 1; it < 2; it++) {
          if (it) {
            const uint64_t dA = mkdesc(sb, 1024, 128, 0), dB = mkdesc(sb + wg * 1280, 2560, 128, 0);
            const int pj = n < 2 ? 6 : 6 - 2 * n;
#pragma unroll 1
            for (int pc = 0; pc < 8; pc++) {
              if (pc == 2) { WG_WAIT(0); if (lane == 0) mbar_arrive(BAR(B_REL3 + 1)); }
              mbar_wait2(BAR(B_FB3 + pc), BAR(pc < 2 ? B_PST : B_PART - 2 + pc), 0, pc >= 2);
              TS3(w == 0 ? 50 + pc + 20 * wg : 127);
              uint64_t da = dA + ((offA3(pc >> 1) + (pc & 1) * 14336) >> 4), db = dB + (offB3(pc) >> 4);
              WG_FENCE();
              if (pc != pj) { wg80_nn(o, da, db); wg80_nn(o, da + 128, db + 320); }
#pragma unroll
              for (int t = 2; t < 7; t++) wg80_nn(o, da + t * 128, db + t * 320);
              WG_COMMIT();
              WG_WAIT(1);
              if ((pc & ~2) && lane == 0) mbar_arrive(BAR(B_REL3 + pc - 1));
              TS3(w == 0 ? 10 + pc + 10 * wg : 127);
            }
            mbar_wait(BAR(B_X1), 0);
            mbar_wait(BAR(B_FIN), 0);
            mbar_wait(BAR(B_REL3 + 5), 0);
          }
          const uint32_t xa = sb + SM_XA + wg * 10240 + ((mi >> 1) * 8 + rr) * 128 + (((2 * w + (mi & 1)) ^ rr) << 4);
          const uint32_t oa = it ? sb + SM_OUT + wg * 10240 + (16 * w + (mi & 1) * 8 + rr) * 160 + (mi >> 1) * 16 : sb + SM_DUMMY, os = it ? 16 : 0;
          uint32_t x[20];
#pragma unroll
          for (int j = 0; j < 5; j++) ldsm4t(xa + j * 2048, x[4 * j], x[4 * j + 1], x[4 * j + 2], x[4 * j + 3]);
          WG_WAIT(0);
          TS3(warp == 0 ? 45 : 127);
#pragma unroll
          for (int j = 0; j < 10; j += 2) {
            const float4 ga = lds128f(sb + SM_SILU + (wg * 80 + 8 * j + 2 * q) * 8), gb = lds128f(sb + SM_SILU + (wg * 80 + 8 * j + 8 + 2 * q) * 8);
            const uint32_t x0 = x[2 * j], x1 = x[2 * j + 1], x2 = x[2 * j + 2], x3 = x[2 * j + 3];
            stsm4(oa + j * os, pack2(fmaf(ga.x, o[4 * j], blo(x0) * ga.y), fmaf(ga.z, o[4 * j + 1], bhi(x0) * ga.w)), pack2(fmaf(ga.x, o[4 * j + 2], blo(x1) * ga.y), fmaf(ga.z, o[4 * j + 3], bhi(x1) * ga.w)),
                  pack2(fmaf(gb.x, o[4 * j + 4], blo(x2) * gb.y), fmaf(gb.z, o[4 * j + 5], bhi(x2) * gb.w)), pack2(fmaf(gb.x, o[4 * j + 6], blo(x3) * gb.y), fmaf(gb.z, o[4 * j + 7], bhi(x3) * gb.w)));
          }
          fence_async_s();
          bar_sync(4 + wg, 128);
        }
        if (t128 == 0) { tma2d_store(&tm_out, n * 160 + wg * 80, m * 64, sb + SM_OUT + wg * 10240); bulk_commit(); bulk_wait_read0(); }
        TS3(w == 0 ? 46 + wg : 127);
      }
    }
  } else if (wg == 2) {
    asm volatile("setmaxnreg.dec.sync.aligned.u32 88;");
    TS1(w == 0 ? 120 : 127);
    mbar_wait(BAR(B_EP), 0);
    TS1(w == 0 ? 121 : 127);
    const unsigned tag = lds32(sb + SM_EP), par = tag & 1;
    mbar_wait(BAR(B_SH), 0);
#pragma unroll 1
    for (int s = w >> 1; s < 5; s += 2) {
      const int blk = tid & 3, quad = (tid >> 2) & 15, ch = s * 128 + (bid & 1) * 64;
      const uint4 sk0 = lds128(sb + SM_SHIFT + ch * 8 + quad * 32), sk1 = lds128(sb + SM_SHIFT + ch * 8 + quad * 32 + 16);
      const uint32_t wa0 = __byte_perm(sk0.x, sk0.z, 0x5410), wa1 = __byte_perm(sk0.x, sk0.z, 0x7632), wa2 = __byte_perm(sk0.y, sk0.w, 0x5410), wa3 = __byte_perm(sk0.y, sk0.w, 0x7632);
      const uint32_t wb0 = __byte_perm(sk1.x, sk1.z, 0x5410), wb1 = __byte_perm(sk1.x, sk1.z, 0x7632), wb2 = __byte_perm(sk1.y, sk1.w, 0x5410), wb3 = __byte_perm(sk1.y, sk1.w, 0x7632);
      uint32_t o0[8], o1[8];
      uint2 kk[11], vv[8];
      const uint32_t so = sb + s * 16384 + blk * 1024 + quad * 8;
      mbar_wait(BAR(B_KV + s), 0);
      TS1(w & 1 ? 127 : 1 + s);
      if (EARLY_A && (tid & 63) == 32) red_relaxed(G->cnt + (C_A + s) * 32);
#pragma unroll
      for (int i = 0; i < 11; i++) kk[i] = lds64(so + i * 128);
#pragma unroll
      for (int i = 0; i < 8; i++) vv[i] = lds64(so + KV_V + i * 128);
#pragma unroll
      for (int i = 0; i < 8; i++) {
        o0[i] = bmul2(bfma2(kk[i + 3].x, wa0, bfma2(kk[i + 2].x, wa1, bfma2(kk[i + 1].x, wa2, bmul2(kk[i].x, wa3)))), vv[i].x);
        o1[i] = bmul2(bfma2(kk[i + 3].y, wb0, bfma2(kk[i + 2].y, wb1, bfma2(kk[i + 1].y, wb2, bmul2(kk[i].y, wb3)))), vv[i].y);
      }
      o0[1] = (o0[1] & 0xfffefffeu) | (par * 0x10001u); o1[1] = (o1[1] & 0xfffefffeu) | (par * 0x10001u);
      uint4* d = G->T + (ch + quad * 4) * 256 + 255 - (bid >> 1) * 4 - blk;
      d[0] = make_uint4(__byte_perm(o0[1], o0[0], 0x5410), __byte_perm(o0[3], o0[2], 0x5410), __byte_perm(o0[5], o0[4], 0x5410), __byte_perm(o0[7], o0[6], 0x5410));
      d[256] = make_uint4(__byte_perm(o0[1], o0[0], 0x7632), __byte_perm(o0[3], o0[2], 0x7632), __byte_perm(o0[5], o0[4], 0x7632), __byte_perm(o0[7], o0[6], 0x7632));
      d[512] = make_uint4(__byte_perm(o1[1], o1[0], 0x5410), __byte_perm(o1[3], o1[2], 0x5410), __byte_perm(o1[5], o1[4], 0x5410), __byte_perm(o1[7], o1[6], 0x5410));
      d[768] = make_uint4(__byte_perm(o1[1], o1[0], 0x7632), __byte_perm(o1[3], o1[2], 0x7632), __byte_perm(o1[5], o1[4], 0x7632), __byte_perm(o1[7], o1[6], 0x7632));
      if (!EARLY_A) { bar_sync(2 + (w >> 1), 64); if ((tid & 63) == 32) red_relaxed(G->cnt + (C_A + s) * 32); }
      TS1(w & 1 ? 70 + s : 127);
      __syncwarp();
      if ((s >> 1) == QPOS) {
      float su[8];
#pragma unroll
      for (int i = 0; i < 8; i++) su[i] = 0.f;
      asm volatile("barrier.cluster.wait.aligned;" ::: "memory");
      mbar_wait(BAR(B_Q), 0);
      TS1(w == 0 ? 6 : 127);
#pragma unroll 1
      for (int g = w * 5; g < w * 5 + 5; g++) {
#pragma unroll
        for (int hh = 0; hh < 2; hh++) {
          uint32_t a0, a1, a2, a3;
          ldsm4(sb + SM_QIN + (g >> 2) * 4096 + (hh * 16 + rr + (mi & 1) * 8) * 128 + (((2 * (g & 3) + (mi >> 1)) ^ rr) << 4), a0, a1, a2, a3);
          stsm4t(sb + SM_QOUT + (g * 16 + rr + (mi >> 1) * 8) * 64 + (((hh * 2 + (mi & 1)) ^ (rr >> 1)) << 4), a0, a1, a2, a3);
          float* u = su + hh * 4;
          u[0] += (blo(a0) + bhi(a0)) + (blo(a2) + bhi(a2)); u[1] = fmaf(blo(a0), blo(a0), fmaf(bhi(a0), bhi(a0), fmaf(blo(a2), blo(a2), fmaf(bhi(a2), bhi(a2), u[1]))));
          u[2] += (blo(a1) + bhi(a1)) + (blo(a3) + bhi(a3)); u[3] = fmaf(blo(a1), blo(a1), fmaf(bhi(a1), bhi(a1), fmaf(blo(a3), blo(a3), fmaf(bhi(a3), bhi(a3), u[3]))));
        }
      }
      TS1(w == 0 ? 85 : 127);
      bfly<8>(su, lane, 2); bfly<4>(su, lane, 1);
      asm volatile("st.async.weak.shared::cluster.mbarrier::complete_tx::bytes.v2.f32 [%0], {%1, %2}, [%3];"
                   ::"r"(mapa(sb + SM_QRED + ((crank * 4 + w) * 16 + (q & 1) * 8 + r) * 8, q >> 1)), "f"(su[0]), "f"(su[1]), "r"(mapa(BAR(B_QS), q >> 1)) : "memory");
      bar_sync(1, 128);
      if (w >= 2) {
#pragma unroll 1
        for (int e = 0; e < 5; e++) {
#pragma unroll
          for (int i = 0; i < 4; i++) {
            uint4 x = lds128(sb + SM_QOUT + (e * 64 + i * 16 + quad) * 64 + ((blk ^ ((quad >> 1) & 3)) << 4));
            x.x = tagw(x.x, par);
            G->T[(640 + e * 128 + (bid & 1) * 64 + i * 16 + quad) * 256 + (bid >> 1) * 4 + blk] = x;
          }
        }
      }
      }
      if (s >= 3) { bar_sync(2 + (w >> 1), 64); if ((tid & 63) == 32) mbar_arrive(BAR(B_R012)); __syncwarp(); }
    }
    {
      mbar_wait(BAR(B_MT), 0);
      mbar_wait(BAR(B_QH), 0);
      TS1(w == 0 ? 8 : 127);
      const uint4* qp = G->T + (640 + bid) * 256 + t128;
      uint4 qn0 = ld_relaxed4(qp), qn1 = ld_relaxed4(qp + 128);
      uint32_t rs[8], ms[8];
      {
        const uint4* sp = (const uint4*)G->qst + t128 * 2;
        uint4 a[4];
        mbar_wait(BAR(B_QO), 0);
#pragma unroll
        for (int i = 0; i < 4; i++) {
          a[i] = lds128(sb + SM_SP + 8192 + (i >> 1) * 4096 + t128 * 32 + (i & 1) * 16);
#pragma unroll 1
          while ((((a[i].x ^ par) | (a[i].y ^ par)) | ((a[i].z ^ par) | (a[i].w ^ par))) & 1) a[i] = ld_relaxed4(sp + (i >> 1) * 256 + (i & 1));
        }
#pragma unroll
        for (int i = 0; i < 4; i++) {
          rs[2 * i] = __byte_perm(a[i].x, a[i].y, 0x7632); ms[2 * i] = __byte_perm(a[i].x, a[i].y, 0x5410);
          rs[2 * i + 1] = __byte_perm(a[i].z, a[i].w, 0x7632); ms[2 * i + 1] = __byte_perm(a[i].z, a[i].w, 0x5410);
        }
      }
#pragma unroll 1
      for (int e = 0; e < 5; e++) {
        const uint4 mt = lds128(sb + SM_MODTAB + e * 16);
        const uint32_t sa = mt.x, ca = mt.y, ga = mt.z, cb = mt.w;
        TS1(w == 0 ? 50 + e : 127);
        const uint4 qv[2] = {ld_fresh(qp, qn0, par), ld_fresh(qp + 128, qn1, par)};
        qp += 128 * 256;
        mbar_wait(BAR(B_PART + e), 0);
        if (EARLY_B && t128 == 32) red_relaxed(G->cnt + (C_B + e) * 32);
        if (e < 4) { qn0 = ld_relaxed4(qp); qn1 = ld_relaxed4(qp + 128); }
        const uint32_t pl = sb + e * 16384 + t128 * 16;
        uint4* ap = G->apT + (e * 128 + bid) * APP + t128;
#pragma unroll
        for (int i = 0; i < 2; i++) {
          const uint4 p0 = lds128(pl + i * 2048), p1 = lds128(pl + 4096 + i * 2048), p2 = lds128(pl + 8192 + i * 2048), p3 = lds128(pl + 12288 + i * 2048);
          const uint32_t y[4] = {badd2(badd2(p0.x, p1.x), badd2(p2.x, p3.x)), badd2(badd2(p0.y, p1.y), badd2(p2.y, p3.y)), badd2(badd2(p0.z, p1.z), badd2(p2.z, p3.z)), badd2(badd2(p0.w, p1.w), badd2(p2.w, p3.w))};
          const uint32_t qa[4] = {qv[i].x, qv[i].y, qv[i].z, qv[i].w};
          uint32_t ao[4];
#pragma unroll
          for (int j = 0; j < 4; j++) ao[j] = bmul2(bfma2(ga, bmul2(bfma2(bfma2(qa[j], rs[4 * i + j], ms[4 * i + j]), ca, sa), y[j]), qa[j]), cb);
          const uint32_t tm = 1u << (bid & 3);
          ap[i * 128] = make_uint4((ao[0] & ~(tm & 1)) | (par & tm), (ao[1] & ~((tm >> 1) & 1)) | (par & (tm >> 1)), (ao[2] & ~((tm >> 2) & 1)) | (par & (tm >> 2)), (ao[3] & ~(tm >> 3)) | (par & (tm >> 3)));
        }
        bar_sync(1, 128);
        if (t128 == 32) { if (!EARLY_B) red_relaxed(G->cnt + (C_B + e) * 32); mbar_arrive(BAR(B_EPI + e)); }
        TS1(w == 0 ? 55 + e : 127);
      }
    }
    if (STOP_AFTER >= 2) {
      wait_cnt(G, C_CLR, tag * 132u);
#pragma unroll 1
      for (int part = 0; part < 2; part++) {
        if (part) {
          if (STOP_AFTER < 3) break;
#pragma unroll 1
          for (int i = t128; i < 160; i += 128) {
            const unsigned* g = (const unsigned*)(G->gbp + ((n * 160 + i) >> 6) * 32) + ((n * 160 + i) & 63);
            unsigned a, b;
#pragma unroll 1
            for (;;) { a = ld_relaxed(g); b = ld_relaxed(g + 64); if (max(a, b) != 0xffffffffu) break; __nanosleep(200); }
            sts64f(sb + SM_SILU + i * 8, bround(__uint_as_float(a) + __uint_as_float(b)), ldcg32f((const float*)G->ic + n * 160 + i));
          }
          mbar_arrive(BAR(B_FIN));
        } else {
#pragma unroll 1
          for (int vt = 0; vt < 2; vt++) {
           if (t128 < 112) {
            const uint4* vp = G->v + (vt * 4 + n) * 112 + t128;
            uint4 x, y;
#pragma unroll 1
            do { x = ld_relaxed4(vp); y = ld_relaxed4(vp + 896); } while (!(valid4(x) && valid4(y)));
            const uint32_t o = sb + (vt ? SM_VT1 : SM_VT2) + t128 * 32;
            if (vt) mbar_wait(BAR(B_Z1OK), 0);
            float a = __uint_as_float(x.x) + __uint_as_float(y.x), b = __uint_as_float(x.y) + __uint_as_float(y.y), ah = bround(a), bh = bround(b);
            sts128(o, make_uint4(pack2(ah, a - ah), pack2(ah, bh), pack2(b - bh, bh), 0u));
            a = __uint_as_float(x.z) + __uint_as_float(y.z); b = __uint_as_float(x.w) + __uint_as_float(y.w); ah = bround(a); bh = bround(b);
            sts128(o + 16, make_uint4(pack2(ah, a - ah), pack2(ah, bh), pack2(b - bh, bh), 0u));
            fence_async_s();
            mbar_arrive(BAR(B_VT));
            TS2(w == 0 ? 65 + vt : 127);
           }
            __syncwarp();
            if (vt) break;
            mbar_wait(BAR(B_LN), 0);
            const uint32_t a = sb + SM_ST2 + q * 512 + (w * 16 + r) * 4;
            const float m0 = quad_sum(lds32f(a)) * (1.f / 640.f), m1 = quad_sum(lds32f(a + 32)) * (1.f / 640.f);
            const float v0 = fmaxf(quad_sum(lds32f(a + 256)) * (1.f / 640.f) - m0 * m0, 0.f) + 1e-5f, v1 = fmaxf(quad_sum(lds32f(a + 288)) * (1.f / 640.f) - m1 * m1, 0.f) + 1e-5f;
            const float h0 = rsqrtf(v0), h1 = rsqrtf(v1);
            sts128(sb + SM_LN2 + t128 * 16, make_uint4(ext_frag(m0, v0 * h0, q), ext_frag(m1, v1 * h1, q), __float_as_uint(h0 * 0.7978845608028f), __float_as_uint(h1 * 0.7978845608028f)));
            sts128f(sb + SM_LN2 + 2048 + t128 * 16, h0 * h0 * h0 * 0.0356774081363f, h1 * h1 * h1 * 0.0356774081363f, v0 * h0, v1 * h1);
            mbar_arrive(BAR(B_ST2));
            TS2(w == 0 ? 82 : 127);
          }
        }
        __syncwarp();
        if (part) {
          uint4 x[14];
          uint4* dst = G->P + tile * IMG + t128;
          mbar_wait(BAR(B_PST), 0);
#pragma unroll
          for (int k = 0; k < 14; k++) x[k] = lds128(sb + k * 2048 + t128 * 16);
#pragma unroll
          for (int k = 0; k < 14; k++) {
            dst[k * 128] = x[k];
            if (k == 6 || k == 13) { bar_sync(1, 128); if (t128 < 2) st_relaxed4(G->blk + tile * BLK + (k == 6 ? 36 : 38) + t128, make_uint4(1u, 1u, 1u, 1u)); }
            if (k == 6) { mbar_arrive(BAR(B_PRD)); TS3(w == 0 ? 37 : 127); }
          }
        }
#pragma unroll 1
        for (int i = part * 2; i < (part ? (STOP_AFTER >= 4 ? 8 : 0) : (STOP_AFTER >= 3 ? 5 : 0)); i++) {
          const uint32_t ta = sb + (part ? offA3(i >> 1) + (i & 1) * 14336 : placeB2(i)) + t128 * 32, wo = ((t128 >> 2) & 7) * 4;
          const int nk = part ? (t128 < 64 ? 4 : 3) : 7;
          mbar_wait(BAR(part ? B_CH - 2 + i : B_FULL2 + i), 0);
          unsigned bad = 0;
#pragma unroll
          for (int k = 0; k < 7; k++) if (k < nk) bad |= lds32(ta + k * 4096 + wo) ^ par;
          if (bad & 1) {
            FX(122);
            const uint4* gp = (part ? G->P + (m * 4 + (i < 4 ? n ^ 1 : ((n ^ 2) & 2) - 2 + (i >> 1))) * IMG + (i & 1) * 896 : G->z2n + (n * 32 + g2_kb(i + 1, m)) * IMG) + t128 * 2;
#pragma unroll 1
            for (int k = 0; k < nk; k++) {
#pragma unroll 1
              while ((lds32(ta + k * 4096 + wo) ^ par) & 1) { sts128(ta + k * 4096, ld_relaxed4(gp + k * 256)); sts128(ta + k * 4096 + 16, ld_relaxed4(gp + k * 256 + 1)); }
            }
            fence_async_s();
          }
          mbar_arrive(BAR(part ? B_PART - 2 + i : B_VAL + i));
        }
      }
    }
  } else {
    asm volatile("setmaxnreg.dec.sync.aligned.u32 40;");
    if (w == 0 || w == 3) {
      const int pw = w & 1;
      mbar_wait(BAR(B_EP), 0);
      const unsigned tag = lds32(sb + SM_EP);
      if (pw == 0) {
        if (lane < 20) sts128(sb + offU(lane >> 2) + 4096 + (lane & 3) * 16, make_uint4(0, 0, 0, 0));
        fence_async_s();
        mbar_wait(BAR(B_KV), 0);
#pragma unroll 1
        for (int s = 0; s < 5;) {
          const unsigned rdy = __ballot_sync(0xffffffffu, (int)(ld_relaxed(G->cnt + (C_A + min(lane, 4)) * 32) - tag * 128u) >= 0);
#pragma unroll 1
          for (; s < 5 && ((rdy >> s) & 1); s++) {
            w_expect(BAR(B_U + s), 4096); bulk_g2s(sb + offU(s), G->T + (s * 128 + bid) * 256, 4096, BAR(B_U + s));
            TS1(75 + s);
          }
        }
      } else {
        const uint32_t dsk = ldg16(p.ssmD + min(lane, 4) * 128 + bid);
        if (lane < 5) sts128(sb + offF(lane), make_uint4(0, 0, 0, 0));
#pragma unroll 1
        for (int s = 0; s < 5; s++) {
          const uint32_t fE = sb + offF(s) + 16 + lane * 16;
          const float dk = blo(__shfl_sync(0xffffffffu, dsk, s));
          mbar_wait(BAR(B_F + s), 0);
          TS1(60 + s);
#pragma unroll 4
          for (int i = 0; i < 8; i++) {
            const uint4 e = lds128(fE + i * 512);
            const uint32_t e4 = lds32(fE + i * 512 + 16);
            sts128(fE + 4160 + i * 512, make_uint4(__byte_perm(e.x, e.y, 0x5432), __byte_perm(e.y, e.z, 0x5432), __byte_perm(e.z, e.w, 0x5432), __byte_perm(e.w, e4, 0x5432)));
          }
          if (lane == 0) {
            const uint32_t e = lds32(fE), f0 = pack2(blo(e) + dk, bhi(e));
            sts32(fE, f0);
            sts128(fE + 4160 - 16, make_uint4(0, 0, 0, f0 << 16));
          }
          __syncwarp();
          if (lane == 0) mbar_arrive(BAR(B_FO + s));
        }
      }
      if (STOP_AFTER >= 2) {
        const int c2 = (864 + nstart(n)) & ~63, c1 = nstart(n) & ~63;
#pragma unroll 1
        for (int h = pw; h < 8; h += 2) {
          mbar_wait(BAR(h < 3 ? B_R012 : B_PART + h - 3), 0);
          w_expect(BAR(B_FULL1 + h), 16384); tma3d(sb + SM_R + h * 16384, &tm_w4, c2, h * 32, BAR(B_FULL1 + h));
        }
#pragma unroll 1
        for (int h0 = 8 + pw; h0 < 40; h0 += 8) {
#pragma unroll
          for (int i = 0; i < 8; i += 2) {
            const uint32_t fb = BAR(B_FULL1 + i) + pw * 8;
            const bool z1 = h0 + i >= 20;
            mbar_wait(fb + (B_EMPTY1 - B_FULL1) * 8, ((h0 >> 3) - 1) & 1);
            w_expect(fb, 16384); tma3d(sb + SM_R + (i + pw) * 16384, &tm_w4, z1 ? c1 : c2, (h0 + i) * 32 - (z1 ? 640 : 0), fb);
          }
        }
      }
      if (STOP_AFTER >= 3) {
        unsigned ready = 0;
#pragma unroll 1
        for (int i = 2 - pw; i < 32; i += 2) {
          const int rnd = ((i - 1) * 52) >> 8, st = i - 1 - rnd * 5, kb = g2_kb(i, m);
          if (i == 6) mbar_wait(BAR(B_EMPTY2 + 4), 0);
          mbar_wait(BAR(B_EMPTY2 + st), rnd & 1);
          w_expect(BAR(B_FULL2 + st), 36864); tma2d(sb + placeA2(st), &tm_wsp, kb * 64, m * 64, BAR(B_FULL2 + st));
          if (rnd == 0) {
#pragma unroll 1
            while (ld_relaxed(G->blk + (kb * 4 + n) * BLK + 32) != 1u) {}
            if (ALIGN2 && i == 2) mbar_wait(BAR(B_GATE), 0);
          } else if (!((ready >> kb) & 1)) {
#pragma unroll 1
            do ready = __ballot_sync(0xffffffffu, ld_acquire(G->blk + (lane * 4 + n) * BLK + 34) == 1u); while (!((ready >> kb) & 1));
            fence_async_g();
          }
          if (i <= 2) TS2(90 + i);
          if (i == 6) TS2(105);
          unsigned cnt = 0;
          if (ALIGN2 && i == 1 && lane == 0) asm volatile("atom.relaxed.gpu.global.add.u32 %0, [%1], 1;" : "=r"(cnt) : "l"(G->cnt + (C_G + (bid >> 4)) * 32) : "memory");
          __syncwarp();
          bulk_g2s(sb + placeB2(st), G->z2n + (n * 32 + kb) * IMG, 28672, BAR(B_FULL2 + st));
          if (ALIGN2 && i == 1) {
            if (__shfl_sync(0xffffffffu, cnt, 0) + 1u != tag * 16u) hint_cnt(G, C_G + (bid >> 4), tag * 16u);
            if (lane == 0) mbar_arrive(BAR(B_GATE));
          }
        }
      }
      if (STOP_AFTER >= 4) {
        mbar_wait(BAR(B_WO), 0);
        const uint4* wo = G->wo + n * 17920;
#define PIECE(i, wb, wp) mbar_wait(BAR(wb), wp); TS3(60 + i); w_expect(BAR(B_FB3 + i), 35840); bulk_g2s(sb + offB3(i), wo + i * 2240, 35840, BAR(B_FB3 + i))
        if (pw) {
          PIECE(0, B_EMPTY2 + 1, 0); PIECE(2, B_EMPTY2 + 3, 0); PIECE(3, B_EMPTY2, 1); PIECE(4, B_REL3 + 1, 0); PIECE(5, B_PRD, 0);
          PIECE(6, B_REL3 + 3, 0); PIECE(7, B_REL3 + 3, 0);
          mbar_wait(BAR(B_REL3 + 4), 0); w_expect(BAR(B_X1), 20480); tma2d(sb + SM_XA, &tm_x1, m * 64, n * 160, BAR(B_X1));
        } else {
          PIECE(1, B_EMPTY2 + 2, 0);
          mbar_wait(BAR(B_PST), 0);
          const uint4* fp = G->blk + (m * 4 + (rr < 4 ? n ^ 1 : ((n ^ 2) & 2) - 2 + (rr >> 1))) * BLK + 36 + (lane & 1) * 2;
          unsigned rdy = 0;
#pragma unroll
          for (int c = 2; c < 8; c++) {
            const int src = m * 4 + (c < 4 ? n ^ 1 : ((n ^ 2) & 2) - 2 + (c >> 1));
#pragma unroll 1
            while (!((rdy >> c) & 1)) rdy = __ballot_sync(0xffffffffu, ld_relaxed(fp) == 1u);
            if (c == 4 || c == 6) mbar_wait(BAR(B_REL3 + c - 4), 0);
            if (c == 2 || c == 4) TS3(92 + (c >> 1));
            w_expect(BAR(B_CH - 2 + c), 14336); bulk_g2s(sb + offA3(c >> 1) + (c & 1) * 14336, G->P + src * IMG + (c & 1) * 896, 14336, BAR(B_CH - 2 + c));
          }
        }
      }
    } else if (w == 1) {
      epoch = __reduce_min_sync(0xffffffffu, epoch / (lane == 10 ? 4u : lane == 11 ? 132u : lane == 14 && ALIGN2 && STOP_AFTER >= 3 ? 16u : 128u) + 1u);
      if (lane == 0) { sts32(sb + SM_EP, epoch); mbar_arrive(BAR(B_EP)); mbar_arrive(BAR(B_INIT)); mbar_expect(BAR(B_LN), 2048); asm volatile("mbarrier.arrive.shared::cta.b64 _, [%0], 128;" ::"r"(BAR(B_PART + 5)) : "memory"); }
      TS1(117);
      asm volatile("barrier.cluster.wait.aligned;" ::: "memory");
      if (lds32(sb + SM_EP + 4) != mytpc) __trap();
      if (lane == 0) { tmap_prefetch(&tm_ap); tmap_prefetch(&tm_w4); tmap_prefetch(&tm_wsp); tmap_prefetch(&tm_x1); tmap_prefetch(&tm_out); }
      mbar_wait(BAR(B_CLR), 0);
      hint_cnt(G, C_M, epoch * 128u);
      {
        const unsigned* mp = (const unsigned*)G->modp + min(r, 4) * 3200 + q * 128 + bid;
        unsigned u[5];
#pragma unroll 1
        do {
#pragma unroll
          for (int s = 0; s < 5; s++) u[s] = ld_relaxed(mp + s * 640);
        } while (__any_sync(0xffffffffu, ((u[0] ^ epoch) | (u[1] ^ epoch) | (u[2] ^ epoch) | (u[3] ^ epoch) | (u[4] ^ epoch)) & 1));
        float y = 0.f;
#pragma unroll
        for (int s = 0; s < 5; s++) {
          float x = __uint_as_float(u[s]);
          const float x4 = __shfl_down_sync(0xffffffffu, x, 16);
          if (lane < 4) x += x4;
          x += __shfl_down_sync(0xffffffffu, x, 8);
          x += __shfl_down_sync(0xffffffffu, x, 4);
          x = __shfl_sync(0xffffffffu, x, q);
          if (r == s) y = x;
        }
        y = bround(y);
        if (q == 1) y += 1.f;
        if (q == 3) y = cb_scale(y);
        if (lane < 20) {
          sts32(sb + SM_MODTAB + lane * 4, pack2(y, y));
          if (q == 3) st_relaxed((float*)G->ic + r * 128 + bid, tagw(__float_as_uint(__fdividef(1.f, y)), epoch & 1));
        }
        __syncwarp();
        if (lane == 0) mbar_arrive(BAR(B_MT));
        TS1(81);
      }
      {
        mbar_wait(BAR(B_QS), 0);
        float a = 0.f;
#pragma unroll
        for (int i = 0; i < 8; i++) a += lds32f(sb + SM_QRED + i * 128 + lane * 4);
        const float sq = __shfl_xor_sync(0xffffffffu, a, 1);
        const float mu = a * (1.f / 640.f), rs = rsqrtf(fmaxf(sq * (1.f / 640.f) - mu * mu, 0.f) + 1e-5f);
        if (!(lane & 1)) G->qst[bid * 16 + (lane >> 1)] = tagw(pack2(-mu * rs, rs), epoch & 1);
        __syncwarp();
        if (lane == 0) { red_relaxed(G->cnt + C_Q * 32); mbar_arrive(BAR(B_R012)); }
        TS1(7);
      }
      hint_cnt(G, C_Q, epoch * 128u);
      if (lane == 0) mbar_arrive(BAR(B_QH));
      w_expect(BAR(B_QO), 8192 + 2560); bulk_g2s(sb + SM_SP + 8192, G->qst, 8192, BAR(B_QO)); bulk_g2s(sb + SM_IC, G->ic, 2560, BAR(B_QO));
      mbar_wait(BAR(B_QO), 0);
      if (STOP_AFTER >= 2) {
        const uint32_t par = epoch & 1;
#pragma unroll 1
        for (int s = 0; s < 5; s++) {
          const uint32_t ta = sb + s * 16384 + lane * 16;
          mbar_wait(BAR(B_A + s), 0);
          unsigned bad = 0;
#pragma unroll
          for (int k = 0; k < 32; k++) bad |= lds32(ta + k * 512 + mi * 4) ^ par;
          uint4 ic = lds128(sb + SM_IC + s * 512 + lane * 16);
          if (!fresh4(ic, par)) {
#pragma unroll 1
            do ic = ld_relaxed4(G->ic + s * 32 + lane); while (!fresh4(ic, par));
            sts128(sb + SM_IC + s * 512 + lane * 16, ic);
          }
          if (bad & 1) {
            FX(126);
#pragma unroll 1
            for (int k = 0; k < 32; k++) {
              const uint4* gp = G->apT + (s * 128 + k * 4 + mi) * APP + m * 8 + (rr ^ ((k * 4 + mi) & 7));
#pragma unroll 1
              while ((lds32(ta + k * 512 + mi * 4) ^ par) & 1) sts128(ta + k * 512, ld_relaxed4(gp));
            }
            fence_async_s();
          }
          __syncwarp();
          if (lane == 0) mbar_arrive(BAR(B_AV + s));
        }
      }
      const uint4 one = make_uint4(1u, 1u, 1u, 1u);
      if (STOP_AFTER >= 2) {
        mbar_wait(BAR(B_STG), 0);
        fence_gpu();
        if (lane < 2) st_relaxed4(G->blk + tile * BLK + 34 + lane, one);
        TS2(31);
      }
      if (STOP_AFTER >= 4) { wait_cnt(G, C_W, epoch * 4u); fence_async_g(); if (lane == 0) mbar_arrive(BAR(B_WO)); }
    } else {
      {
        if (lane == 0) tmap_prefetch(&tm_q);
        __syncwarp();
        uint32_t t0 = clk32() + PACE_1;
#pragma unroll 1
        for (int i = 0;; i++) {
          const int it = (int)(((i < 8 ? SEQ0 : i < 16 ? SEQ1 : SEQ2) >> (8 * (i & 7))) & 255), ty = it >> 4, s = it & 15;
          if (ty > 4) break;
          sleep_until(t0);
          if (ty < 2) {
            if (ty == 0) w_expect(BAR(B_KV + s), 8576);
            tma2d(sb + s * 16384 + ty * KV_V, ty ? &tm_v : &tm_k, s * 128 + (bid & 1) * 64, (bid >> 1) * 32 - 3 + 3 * ty, BAR(B_KV + s));
          } else if (ty == 2) {
            w_expect(BAR(B_F + s), 4096);
            bulk_g2s(sb + offF(s) + 16, p.ssmk + (size_t)(s * 128 + bid) * 2048, 4096, BAR(B_F + s));
          } else if (ty == 3) {
            tma2d(sb + SM_QIN + s * 4096, &tm_q, s * 128 + (bid & 1) * 64, (bid >> 1) * 32, BAR(B_Q));
          }
          t0 += ty == 4 ? PACE_W : PACE_D;
        }
      }
      __syncwarp();
      TS1(95);
      mbar_wait_b(BAR(B_INIT), 0);
      st_relaxed4(G->blk + tile * BLK + lane, ones);
      if (lane < 8) st_relaxed4(G->blk + tile * BLK + 32 + lane, ones);
      __syncwarp();
      if (lane == 0) red_release(G->cnt + C_CLR * 32);
      __syncwarp();
      TS1(9);
      if (STOP_AFTER >= 2) {
        const unsigned tag = lds32(sb + SM_EP);
        int spin = 0;
        mbar_wait_b(BAR(B_EPI), 0);
#pragma unroll 1
        for (int s = 0; s < 5;) {
          const unsigned rdy = __ballot_sync(0xffffffffu, (int)(ld_relaxed(G->cnt + (C_B + min(lane, 4)) * 32) - tag * 128u) >= 0);
          if (++spin > (1 << 19)) __trap();
#pragma unroll 1
          for (; s < 5 && ((rdy >> s) & 1); s++) {
            mbar_wait_b(BAR(B_EPI + s), 0);
            w_expect(BAR(B_A + s), 16384);
            tma2d(sb + s * 16384, &tm_ap, m * 64, s * 128, BAR(B_A + s));
            TS2(110 + s);
          }
        }
      }
      if (STOP_AFTER >= 3) {
        uint32_t t0 = clk32();
#pragma unroll 1
        for (int k = 0; k < 8; k++) {
          sleep_until(t0);
          tma2d_prefetch(&tm_wsp, g2_kb(4 * k + n, m) * 64, m * 64);
          if (k == 1) { mbar_wait_b(BAR(B_SPFREE), 0); w_expect(BAR(B_OWN), 8192); tma2d(sb + SM_SP, &tm_wsp, m * 64, m * 64, BAR(B_OWN)); }
          t0 += PF_GAP;
        }
      }
      __syncwarp();
      mbar_wait_b(BAR(B_DONE), 0);
      return;
    }
  }
  __syncwarp();
  if (lane == 0) mbar_arrive(BAR(B_DONE));
}

typedef CUresult (*EncodeFn)(CUtensorMap*, CUtensorMapDataType, cuuint32_t, void*, const cuuint64_t*, const cuuint64_t*, const cuuint32_t*, const cuuint32_t*,
                             CUtensorMapInterleave, CUtensorMapSwizzle, CUtensorMapL2promotion, CUtensorMapFloatOOBfill);

CUtensorMap make_map(EncodeFn enc, const void* ptr, uint64_t cols, uint64_t rows, uint64_t pitch, uint32_t bc, uint32_t br, bool swz, uint32_t groups = 1) {
  CUtensorMap m;
  cuuint64_t gd[3] = {cols, rows, groups}, gs[2] = {pitch, 128};
  cuuint32_t bd[3] = {bc, br, groups}, es[3] = {1, 1, 1};
  enc(&m, CU_TENSOR_MAP_DATA_TYPE_BFLOAT16, groups > 1 ? 3 : 2, const_cast<void*>(ptr), gd, gs, bd, es, CU_TENSOR_MAP_INTERLEAVE_NONE,
      swz ? CU_TENSOR_MAP_SWIZZLE_128B : CU_TENSOR_MAP_SWIZZLE_NONE, CU_TENSOR_MAP_L2_PROMOTION_L2_128B, CU_TENSOR_MAP_FLOAT_OOB_FILL_NONE);
  return m;
}

}

extern "C" void kernel_launch(void* const* d_in, const int* in_sizes, int n_in, void* d_out, int out_size) {
  (void)in_sizes; (void)n_in; (void)out_size;
  void* fn = nullptr;
  cudaDriverEntryPointQueryResult qr;
  cudaGetDriverEntryPoint("cuTensorMapEncodeTiled", &fn, cudaEnableDefault, &qr);
  EncodeFn enc = (EncodeFn)fn;
  Params p;
  p.shiftk = (const __nv_bfloat16*)d_in[3]; p.ssmk = (const __nv_bfloat16*)d_in[4]; p.ssmD = (const __nv_bfloat16*)d_in[5];
  p.bsp = (const __nv_bfloat16*)d_in[9]; p.c = (const __nv_bfloat16*)d_in[11]; p.wmod = (const __nv_bfloat16*)d_in[12];
  void* scr = nullptr;
  cudaGetSymbolAddress(&scr, g_scr);
  p.g = (Scratch*)scr;
  CUtensorMap tm_k = make_map(enc, d_in[1], 640, 2048, 1280, 64, 35, false);
  CUtensorMap tm_v = make_map(enc, d_in[2], 640, 2048, 1280, 64, 32, false);
  CUtensorMap tm_q = make_map(enc, d_in[0], 640, 2048, 1280, 64, 32, true);
  CUtensorMap tm_wm = make_map(enc, d_in[12], 3840, 640, 7680, 64, 128, true);
  CUtensorMap tm_ap = make_map(enc, p.g->apT, 2048, 640, APP * 16, 64, 128, true);
  CUtensorMap tm_x1 = make_map(enc, p.g->apT, 2048, 640, APP * 16, 64, 160, true);
  CUtensorMap tm_w4 = make_map(enc, d_in[7], 1728, 640, 3456, 64, 32, true, 4);
  CUtensorMap tm_wsp = make_map(enc, d_in[8], 2048, 2048, 4096, 64, 64, true);
  CUtensorMap tm_out = make_map(enc, d_out, 640, 2048, 1280, 80, 64, false);
  CUtensorMap tm_wo = make_map(enc, d_in[10], 640, 864, 1280, 64, 128, true);
  cudaFuncSetAttribute(fused_kernel, cudaFuncAttributeMaxDynamicSharedMemorySize, SM_TOTAL);
  cudaLaunchConfig_t cfg = {};
  cfg.gridDim = dim3(132); cfg.blockDim = dim3(512); cfg.dynamicSmemBytes = SM_TOTAL; cfg.stream = cudaStreamPerThread;
  cudaLaunchAttribute at[2];
  at[0].id = cudaLaunchAttributeCooperative; at[0].val.cooperative = 1;
  at[1].id = cudaLaunchAttributeClusterDimension; at[1].val.clusterDim.x = 2; at[1].val.clusterDim.y = 1; at[1].val.clusterDim.z = 1;
  cfg.attrs = at; cfg.numAttrs = 2;
  cudaLaunchKernelEx(&cfg, fused_kernel, p, tm_k, tm_v, tm_q, tm_wm, tm_ap, tm_x1, tm_w4, tm_wsp, tm_out, tm_wo);
}
```

```cpp
#include <cuda_runtime.h>
#include <cuda.h>
#include <cuda_bf16.h>
#include <stdint.h>
#include <string.h>
#include <stddef.h>

#define SEQ0 0x1202211101201000ull
#define SEQ1 0x3024231404221303ull
#define HSEQ 0x53221
#define SEQ2 0x4342414034333231ull
#define SEQ3 0x44ull
#define T_2 800
#define NPF 4
#define PACE_D 390
#define PACE_Q 355
#define PACE_W 555
#define T_WIN 9800
#define T_SPARE 9000
#define T_PF 13000
#define PF_GAP 1300
#define FLAG_AT 16
#define LOAD_AT 10
#define PUB_AT 20
#define WAIT1 300
#define GATE 0
#define HINT_A 2
#define CSTG 0
#define RDV0 9
#define BULK_A 1
#define CHAIN 1
#define GATEZ 0
#define HOLD_B 0
#define POLL0 0
#define PFENCE 1
#define ROT 0
#define WARM 6
#define STOP_AFTER 99

namespace {

template<int N> struct WRS;
template<int N, int TA, int TB> struct WSS;
template<> struct WRS<16> { static __device__ __forceinline__ void mma(float* d, const uint32_t* a, uint64_t db) {
  asm volatile("wgmma.mma_async.sync.aligned.m64n16k16.f32.bf16.bf16 {%0,%1,%2,%3,%4,%5,%6,%7}, {%8,%9,%10,%11}, %12, 1, 1, 1, 0;"
    : "+f"(d[0]),"+f"(d[1]),"+f"(d[2]),"+f"(d[3]),"+f"(d[4]),"+f"(d[5]),"+f"(d[6]),"+f"(d[7])
    : "r"(a[0]), "r"(a[1]), "r"(a[2]), "r"(a[3]), "l"(db)); } };
template<> struct WRS<32> { static __device__ __forceinline__ void mma(float* d, const uint32_t* a, uint64_t db) {
  asm volatile("wgmma.mma_async.sync.aligned.m64n32k16.f32.bf16.bf16 {%0,%1,%2,%3,%4,%5,%6,%7,%8,%9,%10,%11,%12,%13,%14,%15}, {%16,%17,%18,%19}, %20, 1, 1, 1, 0;"
    : "+f"(d[0]),"+f"(d[1]),"+f"(d[2]),"+f"(d[3]),"+f"(d[4]),"+f"(d[5]),"+f"(d[6]),"+f"(d[7]),"+f"(d[8]),"+f"(d[9]),"+f"(d[10]),"+f"(d[11]),"+f"(d[12]),"+f"(d[13]),"+f"(d[14]),"+f"(d[15])
    : "r"(a[0]), "r"(a[1]), "r"(a[2]), "r"(a[3]), "l"(db)); } };
template<> struct WRS<48> { static __device__ __forceinline__ void mma(float* d, const uint32_t* a, uint64_t db) {
  asm volatile("wgmma.mma_async.sync.aligned.m64n48k16.f32.bf16.bf16 {%0,%1,%2,%3,%4,%5,%6,%7,%8,%9,%10,%11,%12,%13,%14,%15,%16,%17,%18,%19,%20,%21,%22,%23}, {%24,%25,%26,%27}, %28, 1, 1, 1, 0;"
    : "+f"(d[0]),"+f"(d[1]),"+f"(d[2]),"+f"(d[3]),"+f"(d[4]),"+f"(d[5]),"+f"(d[6]),"+f"(d[7]),"+f"(d[8]),"+f"(d[9]),"+f"(d[10]),"+f"(d[11]),"+f"(d[12]),"+f"(d[13]),"+f"(d[14]),"+f"(d[15]),"+f"(d[16]),"+f"(d[17]),"+f"(d[18]),"+f"(d[19]),"+f"(d[20]),"+f"(d[21]),"+f"(d[22]),"+f"(d[23])
    : "r"(a[0]), "r"(a[1]), "r"(a[2]), "r"(a[3]), "l"(db)); } };
template<> struct WRS<64> { static __device__ __forceinline__ void mma(float* d, const uint32_t* a, uint64_t db) {
  asm volatile("wgmma.mma_async.sync.aligned.m64n64k16.f32.bf16.bf16 {%0,%1,%2,%3,%4,%5,%6,%7,%8,%9,%10,%11,%12,%13,%14,%15,%16,%17,%18,%19,%20,%21,%22,%23,%24,%25,%26,%27,%28,%29,%30,%31}, {%32,%33,%34,%35}, %36, 1, 1, 1, 0;"
    : "+f"(d[0]),"+f"(d[1]),"+f"(d[2]),"+f"(d[3]),"+f"(d[4]),"+f"(d[5]),"+f"(d[6]),"+f"(d[7]),"+f"(d[8]),"+f"(d[9]),"+f"(d[10]),"+f"(d[11]),"+f"(d[12]),"+f"(d[13]),"+f"(d[14]),"+f"(d[15]),"+f"(d[16]),"+f"(d[17]),"+f"(d[18]),"+f"(d[19]),"+f"(d[20]),"+f"(d[21]),"+f"(d[22]),"+f"(d[23]),"+f"(d[24]),"+f"(d[25]),"+f"(d[26]),"+f"(d[27]),"+f"(d[28]),"+f"(d[29]),"+f"(d[30]),"+f"(d[31])
    : "r"(a[0]), "r"(a[1]), "r"(a[2]), "r"(a[3]), "l"(db)); } };
template<> struct WRS<80> { static __device__ __forceinline__ void mma(float* d, const uint32_t* a, uint64_t db) {
  asm volatile("wgmma.mma_async.sync.aligned.m64n80k16.f32.bf16.bf16 {%0,%1,%2,%3,%4,%5,%6,%7,%8,%9,%10,%11,%12,%13,%14,%15,%16,%17,%18,%19,%20,%21,%22,%23,%24,%25,%26,%27,%28,%29,%30,%31,%32,%33,%34,%35,%36,%37,%38,%39}, {%40,%41,%42,%43}, %44, 1, 1, 1, 0;"
    : "+f"(d[0]),"+f"(d[1]),"+f"(d[2]),"+f"(d[3]),"+f"(d[4]),"+f"(d[5]),"+f"(d[6]),"+f"(d[7]),"+f"(d[8]),"+f"(d[9]),"+f"(d[10]),"+f"(d[11]),"+f"(d[12]),"+f"(d[13]),"+f"(d[14]),"+f"(d[15]),"+f"(d[16]),"+f"(d[17]),"+f"(d[18]),"+f"(d[19]),"+f"(d[20]),"+f"(d[21]),"+f"(d[22]),"+f"(d[23]),"+f"(d[24]),"+f"(d[25]),"+f"(d[26]),"+f"(d[27]),"+f"(d[28]),"+f"(d[29]),"+f"(d[30]),"+f"(d[31]),"+f"(d[32]),"+f"(d[33]),"+f"(d[34]),"+f"(d[35]),"+f"(d[36]),"+f"(d[37]),"+f"(d[38]),"+f"(d[39])
    : "r"(a[0]), "r"(a[1]), "r"(a[2]), "r"(a[3]), "l"(db)); } };
template<> struct WRS<96> { static __device__ __forceinline__ void mma(float* d, const uint32_t* a, uint64_t db) {
  asm volatile("wgmma.mma_async.sync.aligned.m64n96k16.f32.bf16.bf16 {%0,%1,%2,%3,%4,%5,%6,%7,%8,%9,%10,%11,%12,%13,%14,%15,%16,%17,%18,%19,%20,%21,%22,%23,%24,%25,%26,%27,%28,%29,%30,%31,%32,%33,%34,%35,%36,%37,%38,%39,%40,%41,%42,%43,%44,%45,%46,%47}, {%48,%49,%50,%51}, %52, 1, 1, 1, 0;"
    : "+f"(d[0]),"+f"(d[1]),"+f"(d[2]),"+f"(d[3]),"+f"(d[4]),"+f"(d[5]),"+f"(d[6]),"+f"(d[7]),"+f"(d[8]),"+f"(d[9]),"+f"(d[10]),"+f"(d[11]),"+f"(d[12]),"+f"(d[13]),"+f"(d[14]),"+f"(d[15]),"+f"(d[16]),"+f"(d[17]),"+f"(d[18]),"+f"(d[19]),"+f"(d[20]),"+f"(d[21]),"+f"(d[22]),"+f"(d[23]),"+f"(d[24]),"+f"(d[25]),"+f"(d[26]),"+f"(d[27]),"+f"(d[28]),"+f"(d[29]),"+f"(d[30]),"+f"(d[31]),"+f"(d[32]),"+f"(d[33]),"+f"(d[34]),"+f"(d[35]),"+f"(d[36]),"+f"(d[37]),"+f"(d[38]),"+f"(d[39]),"+f"(d[40]),"+f"(d[41]),"+f"(d[42]),"+f"(d[43]),"+f"(d[44]),"+f"(d[45]),"+f"(d[46]),"+f"(d[47])
    : "r"(a[0]), "r"(a[1]), "r"(a[2]), "r"(a[3]), "l"(db)); } };
template<> struct WRS<112> { static __device__ __forceinline__ void mma(float* d, const uint32_t* a, uint64_t db) {
  asm volatile("wgmma.mma_async.sync.aligned.m64n112k16.f32.bf16.bf16 {%0,%1,%2,%3,%4,%5,%6,%7,%8,%9,%10,%11,%12,%13,%14,%15,%16,%17,%18,%19,%20,%21,%22,%23,%24,%25,%26,%27,%28,%29,%30,%31,%32,%33,%34,%35,%36,%37,%38,%39,%40,%41,%42,%43,%44,%45,%46,%47,%48,%49,%50,%51,%52,%53,%54,%55}, {%56,%57,%58,%59}, %60, 1, 1, 1, 0;"
    : "+f"(d[0]),"+f"(d[1]),"+f"(d[2]),"+f"(d[3]),"+f"(d[4]),"+f"(d[5]),"+f"(d[6]),"+f"(d[7]),"+f"(d[8]),"+f"(d[9]),"+f"(d[10]),"+f"(d[11]),"+f"(d[12]),"+f"(d[13]),"+f"(d[14]),"+f"(d[15]),"+f"(d[16]),"+f"(d[17]),"+f"(d[18]),"+f"(d[19]),"+f"(d[20]),"+f"(d[21]),"+f"(d[22]),"+f"(d[23]),"+f"(d[24]),"+f"(d[25]),"+f"(d[26]),"+f"(d[27]),"+f"(d[28]),"+f"(d[29]),"+f"(d[30]),"+f"(d[31]),"+f"(d[32]),"+f"(d[33]),"+f"(d[34]),"+f"(d[35]),"+f"(d[36]),"+f"(d[37]),"+f"(d[38]),"+f"(d[39]),"+f"(d[40]),"+f"(d[41]),"+f"(d[42]),"+f"(d[43]),"+f"(d[44]),"+f"(d[45]),"+f"(d[46]),"+f"(d[47]),"+f"(d[48]),"+f"(d[49]),"+f"(d[50]),"+f"(d[51]),"+f"(d[52]),"+f"(d[53]),"+f"(d[54]),"+f"(d[55])
    : "r"(a[0]), "r"(a[1]), "r"(a[2]), "r"(a[3]), "l"(db)); } };
template<> struct WRS<128> { static __device__ __forceinline__ void mma(float* d, const uint32_t* a, uint64_t db) {
  asm volatile("wgmma.mma_async.sync.aligned.m64n128k16.f32.bf16.bf16 {%0,%1,%2,%3,%4,%5,%6,%7,%8,%9,%10,%11,%12,%13,%14,%15,%16,%17,%18,%19,%20,%21,%22,%23,%24,%25,%26,%27,%28,%29,%30,%31,%32,%33,%34,%35,%36,%37,%38,%39,%40,%41,%42,%43,%44,%45,%46,%47,%48,%49,%50,%51,%52,%53,%54,%55,%56,%57,%58,%59,%60,%61,%62,%63}, {%64,%65,%66,%67}, %68, 1, 1, 1, 0;"
    : "+f"(d[0]),"+f"(d[1]),"+f"(d[2]),"+f"(d[3]),"+f"(d[4]),"+f"(d[5]),"+f"(d[6]),"+f"(d[7]),"+f"(d[8]),"+f"(d[9]),"+f"(d[10]),"+f"(d[11]),"+f"(d[12]),"+f"(d[13]),"+f"(d[14]),"+f"(d[15]),"+f"(d[16]),"+f"(d[17]),"+f"(d[18]),"+f"(d[19]),"+f"(d[20]),"+f"(d[21]),"+f"(d[22]),"+f"(d[23]),"+f"(d[24]),"+f"(d[25]),"+f"(d[26]),"+f"(d[27]),"+f"(d[28]),"+f"(d[29]),"+f"(d[30]),"+f"(d[31]),"+f"(d[32]),"+f"(d[33]),"+f"(d[34]),"+f"(d[35]),"+f"(d[36]),"+f"(d[37]),"+f"(d[38]),"+f"(d[39]),"+f"(d[40]),"+f"(d[41]),"+f"(d[42]),"+f"(d[43]),"+f"(d[44]),"+f"(d[45]),"+f"(d[46]),"+f"(d[47]),"+f"(d[48]),"+f"(d[49]),"+f"(d[50]),"+f"(d[51]),"+f"(d[52]),"+f"(d[53]),"+f"(d[54]),"+f"(d[55]),"+f"(d[56]),"+f"(d[57]),"+f"(d[58]),"+f"(d[59]),"+f"(d[60]),"+f"(d[61]),"+f"(d[62]),"+f"(d[63])
    : "r"(a[0]), "r"(a[1]), "r"(a[2]), "r"(a[3]), "l"(db)); } };
template<> struct WRS<192> { static __device__ __forceinline__ void mma(float* d, const uint32_t* a, uint64_t db) {
  asm volatile("wgmma.mma_async.sync.aligned.m64n192k16.f32.bf16.bf16 {%0,%1,%2,%3,%4,%5,%6,%7,%8,%9,%10,%11,%12,%13,%14,%15,%16,%17,%18,%19,%20,%21,%22,%23,%24,%25,%26,%27,%28,%29,%30,%31,%32,%33,%34,%35,%36,%37,%38,%39,%40,%41,%42,%43,%44,%45,%46,%47,%48,%49,%50,%51,%52,%53,%54,%55,%56,%57,%58,%59,%60,%61,%62,%63,%64,%65,%66,%67,%68,%69,%70,%71,%72,%73,%74,%75,%76,%77,%78,%79,%80,%81,%82,%83,%84,%85,%86,%87,%88,%89,%90,%91,%92,%93,%94,%95}, {%96,%97,%98,%99}, %100, 1, 1, 1, 0;"
    : "+f"(d[0]),"+f"(d[1]),"+f"(d[2]),"+f"(d[3]),"+f"(d[4]),"+f"(d[5]),"+f"(d[6]),"+f"(d[7]),"+f"(d[8]),"+f"(d[9]),"+f"(d[10]),"+f"(d[11]),"+f"(d[12]),"+f"(d[13]),"+f"(d[14]),"+f"(d[15]),"+f"(d[16]),"+f"(d[17]),"+f"(d[18]),"+f"(d[19]),"+f"(d[20]),"+f"(d[21]),"+f"(d[22]),"+f"(d[23]),"+f"(d[24]),"+f"(d[25]),"+f"(d[26]),"+f"(d[27]),"+f"(d[28]),"+f"(d[29]),"+f"(d[30]),"+f"(d[31]),"+f"(d[32]),"+f"(d[33]),"+f"(d[34]),"+f"(d[35]),"+f"(d[36]),"+f"(d[37]),"+f"(d[38]),"+f"(d[39]),"+f"(d[40]),"+f"(d[41]),"+f"(d[42]),"+f"(d[43]),"+f"(d[44]),"+f"(d[45]),"+f"(d[46]),"+f"(d[47]),"+f"(d[48]),"+f"(d[49]),"+f"(d[50]),"+f"(d[51]),"+f"(d[52]),"+f"(d[53]),"+f"(d[54]),"+f"(d[55]),"+f"(d[56]),"+f"(d[57]),"+f"(d[58]),"+f"(d[59]),"+f"(d[60]),"+f"(d[61]),"+f"(d[62]),"+f"(d[63]),"+f"(d[64]),"+f"(d[65]),"+f"(d[66]),"+f"(d[67]),"+f"(d[68]),"+f"(d[69]),"+f"(d[70]),"+f"(d[71]),"+f"(d[72]),"+f"(d[73]),"+f"(d[74]),"+f"(d[75]),"+f"(d[76]),"+f"(d[77]),"+f"(d[78]),"+f"(d[79]),"+f"(d[80]),"+f"(d[81]),"+f"(d[82]),"+f"(d[83]),"+f"(d[84]),"+f"(d[85]),"+f"(d[86]),"+f"(d[87]),"+f"(d[88]),"+f"(d[89]),"+f"(d[90]),"+f"(d[91]),"+f"(d[92]),"+f"(d[93]),"+f"(d[94]),"+f"(d[95])
    : "r"(a[0]), "r"(a[1]), "r"(a[2]), "r"(a[3]), "l"(db)); } };
template<> struct WSS<192,1,1> { static __device__ __forceinline__ void mma(float* d, uint64_t da, uint64_t db, int acc = 1) {
  asm volatile("{\n.reg .pred p;\nsetp.ne.b32 p, %98, 0;\nwgmma.mma_async.sync.aligned.m64n192k16.f32.bf16.bf16 {%0,%1,%2,%3,%4,%5,%6,%7,%8,%9,%10,%11,%12,%13,%14,%15,%16,%17,%18,%19,%20,%21,%22,%23,%24,%25,%26,%27,%28,%29,%30,%31,%32,%33,%34,%35,%36,%37,%38,%39,%40,%41,%42,%43,%44,%45,%46,%47,%48,%49,%50,%51,%52,%53,%54,%55,%56,%57,%58,%59,%60,%61,%62,%63,%64,%65,%66,%67,%68,%69,%70,%71,%72,%73,%74,%75,%76,%77,%78,%79,%80,%81,%82,%83,%84,%85,%86,%87,%88,%89,%90,%91,%92,%93,%94,%95}, %96, %97, p, 1, 1, 1, 1;\n}"
    : "+f"(d[0]),"+f"(d[1]),"+f"(d[2]),"+f"(d[3]),"+f"(d[4]),"+f"(d[5]),"+f"(d[6]),"+f"(d[7]),"+f"(d[8]),"+f"(d[9]),"+f"(d[10]),"+f"(d[11]),"+f"(d[12]),"+f"(d[13]),"+f"(d[14]),"+f"(d[15]),"+f"(d[16]),"+f"(d[17]),"+f"(d[18]),"+f"(d[19]),"+f"(d[20]),"+f"(d[21]),"+f"(d[22]),"+f"(d[23]),"+f"(d[24]),"+f"(d[25]),"+f"(d[26]),"+f"(d[27]),"+f"(d[28]),"+f"(d[29]),"+f"(d[30]),"+f"(d[31]),"+f"(d[32]),"+f"(d[33]),"+f"(d[34]),"+f"(d[35]),"+f"(d[36]),"+f"(d[37]),"+f"(d[38]),"+f"(d[39]),"+f"(d[40]),"+f"(d[41]),"+f"(d[42]),"+f"(d[43]),"+f"(d[44]),"+f"(d[45]),"+f"(d[46]),"+f"(d[47]),"+f"(d[48]),"+f"(d[49]),"+f"(d[50]),"+f"(d[51]),"+f"(d[52]),"+f"(d[53]),"+f"(d[54]),"+f"(d[55]),"+f"(d[56]),"+f"(d[57]),"+f"(d[58]),"+f"(d[59]),"+f"(d[60]),"+f"(d[61]),"+f"(d[62]),"+f"(d[63]),"+f"(d[64]),"+f"(d[65]),"+f"(d[66]),"+f"(d[67]),"+f"(d[68]),"+f"(d[69]),"+f"(d[70]),"+f"(d[71]),"+f"(d[72]),"+f"(d[73]),"+f"(d[74]),"+f"(d[75]),"+f"(d[76]),"+f"(d[77]),"+f"(d[78]),"+f"(d[79]),"+f"(d[80]),"+f"(d[81]),"+f"(d[82]),"+f"(d[83]),"+f"(d[84]),"+f"(d[85]),"+f"(d[86]),"+f"(d[87]),"+f"(d[88]),"+f"(d[89]),"+f"(d[90]),"+f"(d[91]),"+f"(d[92]),"+f"(d[93]),"+f"(d[94]),"+f"(d[95])
    : "l"(da), "l"(db), "r"(acc)); } };
template<> struct WSS<32,1,1> { static __device__ __forceinline__ void mma(float* d, uint64_t da, uint64_t db, int acc = 1) {
  asm volatile("{\n.reg .pred p;\nsetp.ne.b32 p, %18, 0;\nwgmma.mma_async.sync.aligned.m64n32k16.f32.bf16.bf16 {%0,%1,%2,%3,%4,%5,%6,%7,%8,%9,%10,%11,%12,%13,%14,%15}, %16, %17, p, 1, 1, 1, 1;\n}"
    : "+f"(d[0]),"+f"(d[1]),"+f"(d[2]),"+f"(d[3]),"+f"(d[4]),"+f"(d[5]),"+f"(d[6]),"+f"(d[7]),"+f"(d[8]),"+f"(d[9]),"+f"(d[10]),"+f"(d[11]),"+f"(d[12]),"+f"(d[13]),"+f"(d[14]),"+f"(d[15])
    : "l"(da), "l"(db), "r"(acc)); } };
template<> struct WSS<128,0,1> { static __device__ __forceinline__ void mma(float* d, uint64_t da, uint64_t db, int acc = 1) {
  asm volatile("{\n.reg .pred p;\nsetp.ne.b32 p, %66, 0;\nwgmma.mma_async.sync.aligned.m64n128k16.f32.bf16.bf16 {%0,%1,%2,%3,%4,%5,%6,%7,%8,%9,%10,%11,%12,%13,%14,%15,%16,%17,%18,%19,%20,%21,%22,%23,%24,%25,%26,%27,%28,%29,%30,%31,%32,%33,%34,%35,%36,%37,%38,%39,%40,%41,%42,%43,%44,%45,%46,%47,%48,%49,%50,%51,%52,%53,%54,%55,%56,%57,%58,%59,%60,%61,%62,%63}, %64, %65, p, 1, 1, 0, 1;\n}"
    : "+f"(d[0]),"+f"(d[1]),"+f"(d[2]),"+f"(d[3]),"+f"(d[4]),"+f"(d[5]),"+f"(d[6]),"+f"(d[7]),"+f"(d[8]),"+f"(d[9]),"+f"(d[10]),"+f"(d[11]),"+f"(d[12]),"+f"(d[13]),"+f"(d[14]),"+f"(d[15]),"+f"(d[16]),"+f"(d[17]),"+f"(d[18]),"+f"(d[19]),"+f"(d[20]),"+f"(d[21]),"+f"(d[22]),"+f"(d[23]),"+f"(d[24]),"+f"(d[25]),"+f"(d[26]),"+f"(d[27]),"+f"(d[28]),"+f"(d[29]),"+f"(d[30]),"+f"(d[31]),"+f"(d[32]),"+f"(d[33]),"+f"(d[34]),"+f"(d[35]),"+f"(d[36]),"+f"(d[37]),"+f"(d[38]),"+f"(d[39]),"+f"(d[40]),"+f"(d[41]),"+f"(d[42]),"+f"(d[43]),"+f"(d[44]),"+f"(d[45]),"+f"(d[46]),"+f"(d[47]),"+f"(d[48]),"+f"(d[49]),"+f"(d[50]),"+f"(d[51]),"+f"(d[52]),"+f"(d[53]),"+f"(d[54]),"+f"(d[55]),"+f"(d[56]),"+f"(d[57]),"+f"(d[58]),"+f"(d[59]),"+f"(d[60]),"+f"(d[61]),"+f"(d[62]),"+f"(d[63])
    : "l"(da), "l"(db), "r"(acc)); } };
template<> struct WSS<96,0,1> { static __device__ __forceinline__ void mma(float* d, uint64_t da, uint64_t db, int acc = 1) {
  asm volatile("{\n.reg .pred p;\nsetp.ne.b32 p, %50, 0;\nwgmma.mma_async.sync.aligned.m64n96k16.f32.bf16.bf16 {%0,%1,%2,%3,%4,%5,%6,%7,%8,%9,%10,%11,%12,%13,%14,%15,%16,%17,%18,%19,%20,%21,%22,%23,%24,%25,%26,%27,%28,%29,%30,%31,%32,%33,%34,%35,%36,%37,%38,%39,%40,%41,%42,%43,%44,%45,%46,%47}, %48, %49, p, 1, 1, 0, 1;\n}"
    : "+f"(d[0]),"+f"(d[1]),"+f"(d[2]),"+f"(d[3]),"+f"(d[4]),"+f"(d[5]),"+f"(d[6]),"+f"(d[7]),"+f"(d[8]),"+f"(d[9]),"+f"(d[10]),"+f"(d[11]),"+f"(d[12]),"+f"(d[13]),"+f"(d[14]),"+f"(d[15]),"+f"(d[16]),"+f"(d[17]),"+f"(d[18]),"+f"(d[19]),"+f"(d[20]),"+f"(d[21]),"+f"(d[22]),"+f"(d[23]),"+f"(d[24]),"+f"(d[25]),"+f"(d[26]),"+f"(d[27]),"+f"(d[28]),"+f"(d[29]),"+f"(d[30]),"+f"(d[31]),"+f"(d[32]),"+f"(d[33]),"+f"(d[34]),"+f"(d[35]),"+f"(d[36]),"+f"(d[37]),"+f"(d[38]),"+f"(d[39]),"+f"(d[40]),"+f"(d[41]),"+f"(d[42]),"+f"(d[43]),"+f"(d[44]),"+f"(d[45]),"+f"(d[46]),"+f"(d[47])
    : "l"(da), "l"(db), "r"(acc)); } };
template<> struct WSS<64,0,1> { static __device__ __forceinline__ void mma(float* d, uint64_t da, uint64_t db, int acc = 1) {
  asm volatile("{\n.reg .pred p;\nsetp.ne.b32 p, %34, 0;\nwgmma.mma_async.sync.aligned.m64n64k16.f32.bf16.bf16 {%0,%1,%2,%3,%4,%5,%6,%7,%8,%9,%10,%11,%12,%13,%14,%15,%16,%17,%18,%19,%20,%21,%22,%23,%24,%25,%26,%27,%28,%29,%30,%31}, %32, %33, p, 1, 1, 0, 1;\n}"
    : "+f"(d[0]),"+f"(d[1]),"+f"(d[2]),"+f"(d[3]),"+f"(d[4]),"+f"(d[5]),"+f"(d[6]),"+f"(d[7]),"+f"(d[8]),"+f"(d[9]),"+f"(d[10]),"+f"(d[11]),"+f"(d[12]),"+f"(d[13]),"+f"(d[14]),"+f"(d[15]),"+f"(d[16]),"+f"(d[17]),"+f"(d[18]),"+f"(d[19]),"+f"(d[20]),"+f"(d[21]),"+f"(d[22]),"+f"(d[23]),"+f"(d[24]),"+f"(d[25]),"+f"(d[26]),"+f"(d[27]),"+f"(d[28]),"+f"(d[29]),"+f"(d[30]),"+f"(d[31])
    : "l"(da), "l"(db), "r"(acc)); } };
template<> struct WSS<8,1,0> { static __device__ __forceinline__ void mma(float* d, uint64_t da, uint64_t db, int acc = 1) {
  asm volatile("{\n.reg .pred p;\nsetp.ne.b32 p, %6, 0;\nwgmma.mma_async.sync.aligned.m64n8k16.f32.bf16.bf16 {%0,%1,%2,%3}, %4, %5, p, 1, 1, 1, 0;\n}"
    : "+f"(d[0]),"+f"(d[1]),"+f"(d[2]),"+f"(d[3])
    : "l"(da), "l"(db), "r"(acc)); } };
__device__ __forceinline__ void wrs128_first(float* d, const uint32_t* a, uint64_t db) {
  asm volatile("wgmma.mma_async.sync.aligned.m64n128k16.f32.bf16.bf16 {%0,%1,%2,%3,%4,%5,%6,%7,%8,%9,%10,%11,%12,%13,%14,%15,%16,%17,%18,%19,%20,%21,%22,%23,%24,%25,%26,%27,%28,%29,%30,%31,%32,%33,%34,%35,%36,%37,%38,%39,%40,%41,%42,%43,%44,%45,%46,%47,%48,%49,%50,%51,%52,%53,%54,%55,%56,%57,%58,%59,%60,%61,%62,%63}, {%64,%65,%66,%67}, %68, 0, 1, 1, 0;"
    : "=f"(d[0]),"=f"(d[1]),"=f"(d[2]),"=f"(d[3]),"=f"(d[4]),"=f"(d[5]),"=f"(d[6]),"=f"(d[7]),"=f"(d[8]),"=f"(d[9]),"=f"(d[10]),"=f"(d[11]),"=f"(d[12]),"=f"(d[13]),"=f"(d[14]),"=f"(d[15]),"=f"(d[16]),"=f"(d[17]),"=f"(d[18]),"=f"(d[19]),"=f"(d[20]),"=f"(d[21]),"=f"(d[22]),"=f"(d[23]),"=f"(d[24]),"=f"(d[25]),"=f"(d[26]),"=f"(d[27]),"=f"(d[28]),"=f"(d[29]),"=f"(d[30]),"=f"(d[31]),"=f"(d[32]),"=f"(d[33]),"=f"(d[34]),"=f"(d[35]),"=f"(d[36]),"=f"(d[37]),"=f"(d[38]),"=f"(d[39]),"=f"(d[40]),"=f"(d[41]),"=f"(d[42]),"=f"(d[43]),"=f"(d[44]),"=f"(d[45]),"=f"(d[46]),"=f"(d[47]),"=f"(d[48]),"=f"(d[49]),"=f"(d[50]),"=f"(d[51]),"=f"(d[52]),"=f"(d[53]),"=f"(d[54]),"=f"(d[55]),"=f"(d[56]),"=f"(d[57]),"=f"(d[58]),"=f"(d[59]),"=f"(d[60]),"=f"(d[61]),"=f"(d[62]),"=f"(d[63])
    : "r"(a[0]), "r"(a[1]), "r"(a[2]), "r"(a[3]), "l"(db)); }

constexpr int IMG = 1792;
struct Scratch {
  unsigned cnt[24 * 32];
  float modp[2 * 3200];
  float gb[640];
  uint4 vt[8 * 224];
  uint2 st3[128 * 64];
  unsigned flagE[128 * 32];
  unsigned flagL[128 * 8];
  uint4 T[640 * 256];
  uint4 Y[640 * 256];
  uint4 z2n[4 * 32 * IMG];
};
__device__ __align__(1024) Scratch g_scr;
enum { C_A = 0, C_Y = 10, C_M = 20, C_E = 22 };

constexpr uint32_t SM_R = 81920, SM_PO = 184320, SM_S = 212992, SM_X1 = 221184, SM_TAIL = 229376, SM_TOTAL = 232448;
constexpr uint32_t KV_V = 7168;
constexpr uint32_t SM_VT = SM_S, SM_LN1 = SM_S, SM_MOD = SM_S + 3584, SM_LN2 = SM_S + 6144, SM_SILU = SM_LN2;
constexpr uint32_t SM_BAR = SM_TAIL, SM_TPC = SM_BAR + 912, SM_DUMMY = SM_TPC + 48, SM_LNB = SM_DUMMY + 64, SM_PROF = SM_LNB + 1024, SM_GB = SM_MOD;
static_assert(SM_PROF + 512 <= SM_TOTAL, "smem");
__device__ __forceinline__ uint32_t offU(int s) { return SM_R + ((0x64302u >> (4 * s)) & 15) * 16384; }
__device__ __forceinline__ uint32_t offF(int s) { return offU(s) + 4208; }
__host__ __device__ constexpr uint32_t placeB(int st) { return ((uint32_t)(0x9874245000ull >> (8 * st)) & 255) * 1024; }
__host__ __device__ constexpr uint32_t placeA(int st) { return ((uint32_t)(0x40906C1CD8ull >> (8 * st)) & 255) * 1024; }
__device__ __forceinline__ int nstart(int n) { return n < 3 ? 224 * n : 640; }
enum {
  B_KV = 0, B_F = 5, B_WM = 10, B_Q = 15, B_U = 20, B_YH = 25  , B_AP = 31, B_LN = 36  , B_PP = 38  ,
  B_XF = 40  , B_VT = 42, B_X1D = 43, B_GB = 44, B_ACK = 45, B_EP = 46, B_LF = 47, B_LOK = 48,
  B_FULL1 = 50, B_FULL2 = 54, B_XS = 59,
  B_KVF = 64, B_EMPTY1 = 69, B_EMPTY2 = 73, B_VAL = 78, B_PST = 83  , B_VTF = 85, B_PUB = 86, B_Z1S = 87, B_PFREE = 88, B_NIL = 89,
  B_DONE = 90  , B_AO = 94, B_LNB = 99, B_RF = 100, B_MT = 105, B_WMF = 106, B_FO = 107
};

struct Params {
  const __nv_bfloat16 *k, *v;
  Scratch* g;
  const __nv_bfloat16 *shiftk, *c;
  int by_sm;
  const __nv_bfloat16 *ssmk, *ssmD, *bsp, *wout, *wsp;
  uint8_t tile[64];
};

struct Maps { CUtensorMap k, v, f, wm, q, y, w2, x1, wsp, out, wo; };

__device__ __forceinline__ void mbar_arrive(uint32_t a) { asm volatile("mbarrier.arrive.shared::cta.b64 _, [%0];" ::"r"(a) : "memory"); }
__device__ __forceinline__ void mbar_expect(uint32_t a, int b) { asm volatile("mbarrier.arrive.expect_tx.shared::cta.b64 _, [%0], %1;" ::"r"(a), "r"(b) : "memory"); }
__device__ __forceinline__ void mbar_wait(uint32_t a, int ph) {
  asm volatile("{\n.reg .pred p;\nWL:\nmbarrier.try_wait.parity.shared::cta.b64 p, [%0], %1;\n@!p bra WL;\n}" ::"r"(a), "r"(ph) : "memory");
}
__device__ __forceinline__ void mbar_wait2(uint32_t a, uint32_t b, int pa, int pb) {
  asm volatile("{\n.reg .pred p, q;\nWL:\nmbarrier.try_wait.parity.shared::cta.b64 p, [%0], %2;\nmbarrier.try_wait.parity.shared::cta.b64 q, [%1], %3;\nand.pred p, p, q;\n@!p bra WL;\n}" ::"r"(a), "r"(b), "r"(pa), "r"(pb) : "memory");
}
__device__ __forceinline__ uint32_t mbar_test(uint32_t a, int ph) {
  uint32_t r;
  asm volatile("{\n.reg .pred p;\nmbarrier.test_wait.parity.shared::cta.b64 p, [%1], %2;\nselp.u32 %0, 1, 0, p;\n}" : "=r"(r) : "r"(a), "r"(ph) : "memory");
  return r;
}
__device__ __forceinline__ void mbar_wait_b(uint32_t a, int ph) {
  asm volatile("{\n.reg .pred p;\n.reg .u32 c;\nmov.u32 c, 0;\nWL:\nmbarrier.try_wait.parity.shared::cta.b64 p, [%0], %1;\n@p bra WD;\n"
               "add.u32 c, c, 1;\nsetp.lt.u32 p, c, 0x10000;\n@p bra WL;\ntrap;\nWD:\n}" ::"r"(a), "r"(ph) : "memory");
}
__device__ __forceinline__ uint32_t mapa(uint32_t a, uint32_t rank) { uint32_t r; asm("mapa.shared::cluster.u32 %0, %1, %2;" : "=r"(r) : "r"(a), "r"(rank)); return r; }
__device__ __forceinline__ void bar_sync(int id, int n) { asm volatile("bar.sync %0, %1;" ::"r"(id), "r"(n) : "memory"); }
__device__ __forceinline__ void bar_arrive(int id, int n) { asm volatile("bar.arrive %0, %1;" ::"r"(id), "r"(n) : "memory"); }
__device__ __forceinline__ unsigned ld_acquire(const void* p) { unsigned v; asm volatile("ld.acquire.gpu.global.u32 %0, [%1];" : "=r"(v) : "l"(p) : "memory"); return v; }
__device__ __forceinline__ unsigned ld_relaxed(const void* p) { unsigned v; asm volatile("ld.relaxed.gpu.global.u32 %0, [%1];" : "=r"(v) : "l"(p) : "memory"); return v; }
__device__ __forceinline__ uint4 ld_relaxed4(const void* p) { uint4 v; asm volatile("ld.relaxed.gpu.global.v4.u32 {%0,%1,%2,%3}, [%4];" : "=r"(v.x), "=r"(v.y), "=r"(v.z), "=r"(v.w) : "l"(p) : "memory"); return v; }
__device__ __forceinline__ void st_relaxed4(void* p, uint4 v) { asm volatile("st.relaxed.gpu.global.v4.u32 [%0], {%1,%2,%3,%4};" ::"l"(p), "r"(v.x), "r"(v.y), "r"(v.z), "r"(v.w) : "memory"); }
__device__ __forceinline__ uint2 ld_relaxed2(const void* p) { uint2 v; asm volatile("ld.relaxed.gpu.global.v2.u32 {%0,%1}, [%2];" : "=r"(v.x), "=r"(v.y) : "l"(p) : "memory"); return v; }
__device__ __forceinline__ void st_relaxed2(void* p, uint32_t a, uint32_t b) { asm volatile("st.relaxed.gpu.global.v2.u32 [%0], {%1,%2};" ::"l"(p), "r"(a), "r"(b) : "memory"); }
__device__ __forceinline__ void st_relaxed(void* p, unsigned v) { asm volatile("st.relaxed.gpu.global.u32 [%0], %1;" ::"l"(p), "r"(v) : "memory"); }
__device__ __forceinline__ void fence_gpu() { asm volatile("fence.acq_rel.gpu;" ::: "memory"); }
__device__ __forceinline__ void wait_cnt_b(const Scratch* G, int idx, unsigned target) {
  asm volatile("{\n.reg .pred p;\n.reg .u32 v, c;\nmov.u32 c, 0;\nWL:\nld.acquire.gpu.global.u32 v, [%0];\nsub.s32 v, v, %1;\nsetp.ge.s32 p, v, 0;\n@p bra WD;\n"
               "add.u32 c, c, 1;\nsetp.lt.u32 p, c, 0x80000;\n@p bra WL;\ntrap;\nWD:\n}" ::"l"(G->cnt + idx * 32), "r"(target) : "memory");
}
__device__ __forceinline__ void fence_async_g() { asm volatile("fence.proxy.async.global;" ::: "memory"); }
__device__ __forceinline__ void fence_async_s() { asm volatile("fence.proxy.async.shared::cta;" ::: "memory"); }
#define ELECT "{\n.reg .pred e;\nelect.sync _|e, 0xffffffff;\n@e "
__device__ __forceinline__ void w_expect(uint32_t a, int b) { asm volatile(ELECT "mbarrier.arrive.expect_tx.shared::cta.b64 _, [%0], %1;\n}" ::"r"(a), "r"(b) : "memory"); }
__device__ __forceinline__ void bulk_g2s(uint32_t dst, const void* src, int bytes, uint32_t bar) {
  asm volatile(ELECT "cp.async.bulk.shared::cluster.global.mbarrier::complete_tx::bytes [%0], [%1], %2, [%3];\n}" ::"r"(dst), "l"(src), "r"(bytes), "r"(bar) : "memory");
}
__device__ __forceinline__ void bulk_commit() { asm volatile("cp.async.bulk.commit_group;" ::: "memory"); }
__device__ __forceinline__ void bulk_wait_read0() { asm volatile("cp.async.bulk.wait_group.read 0;" ::: "memory"); }
__device__ __forceinline__ void tma2d(uint32_t dst, const CUtensorMap* m, int c0, int c1, uint32_t bar) {
  asm volatile(ELECT "cp.async.bulk.tensor.2d.shared::cluster.global.mbarrier::complete_tx::bytes [%0], [%1, {%3, %4}], [%2];\n}" ::"r"(dst), "l"(m), "r"(bar), "r"(c0), "r"(c1) : "memory");
}
__device__ __forceinline__ void tma3d(uint32_t dst, const CUtensorMap* m, int c0, int c1, int c2, uint32_t bar) {
  asm volatile(ELECT "cp.async.bulk.tensor.3d.shared::cluster.global.mbarrier::complete_tx::bytes [%0], [%1, {%3, %4, %5}], [%2];\n}" ::"r"(dst), "l"(m), "r"(bar), "r"(c0), "r"(c1), "r"(c2) : "memory");
}
__device__ __forceinline__ void tma_rows(uint32_t dst, const CUtensorMap* m, int c0, int c2, int c3, uint32_t bar) {
  asm volatile(ELECT "cp.async.bulk.tensor.4d.shared::cluster.global.mbarrier::complete_tx::bytes [%0], [%1, {%3, %6, %4, %5}], [%2];\n}" ::"r"(dst), "l"(m), "r"(bar), "r"(c0), "r"(c2), "r"(c3), "r"(0) : "memory");
}
__device__ __forceinline__ void tma_rows_add(const CUtensorMap* m, int c0, int c2, int c3, uint32_t src) {
  asm volatile(ELECT "cp.reduce.async.bulk.tensor.4d.global.shared::cta.add.tile.bulk_group [%0, {%2, %5, %3, %4}], [%1];\n}" ::"l"(m), "r"(src), "r"(c0), "r"(c2), "r"(c3), "r"(0) : "memory");
}
__device__ __forceinline__ void tma5d(uint32_t dst, const CUtensorMap* m, int c0, int c1, int c2, int c3, uint32_t bar) {
  asm volatile(ELECT "cp.async.bulk.tensor.5d.shared::cluster.global.mbarrier::complete_tx::bytes [%0], [%1, {%3, %4, %5, %6, %7}], [%2];\n}" ::"r"(dst), "l"(m), "r"(bar), "r"(c0), "r"(c1), "r"(c2), "r"(c3), "r"(0) : "memory");
}
__device__ __forceinline__ void tma5d_store(const CUtensorMap* m, int c0, int c2, int c3, uint32_t src) {
  asm volatile(ELECT "cp.async.bulk.tensor.5d.global.shared::cta.bulk_group [%0, {%2, %5, %3, %4, %5}], [%1];\n}" ::"l"(m), "r"(src), "r"(c0), "r"(c2), "r"(c3), "r"(0) : "memory");
}
__device__ __forceinline__ void bulk_s2peer(uint32_t rdst, uint32_t src, int bytes, uint32_t rbar) {
  asm volatile(ELECT "cp.async.bulk.shared::cluster.shared::cta.mbarrier::complete_tx::bytes [%0], [%1], %2, [%3];\n}" ::"r"(rdst), "r"(src), "r"(bytes), "r"(rbar) : "memory");
}
__device__ __forceinline__ void w_count(const Scratch* G, int idx) { asm volatile(ELECT "red.relaxed.gpu.global.add.u32 [%0], 1;\n}" ::"l"(G->cnt + idx * 32) : "memory"); }
__device__ __forceinline__ void w_arrive(uint32_t a) { asm volatile(ELECT "mbarrier.arrive.shared::cta.b64 _, [%0];\n}" ::"r"(a) : "memory"); }
__device__ __forceinline__ void w_arrive_peer(uint32_t ra) { asm volatile(ELECT "mbarrier.arrive.shared::cluster.b64 _, [%0];\n}" ::"r"(ra) : "memory"); }
__device__ __forceinline__ void tmap_prefetch(const CUtensorMap* m) { asm volatile("prefetch.tensormap [%0];" ::"l"(m) : "memory"); }
__device__ __forceinline__ uint64_t mkdesc(uint32_t addr, uint32_t lbo, uint32_t sbo, uint32_t swz) {
  return (uint64_t)((addr & 0x3FFFF) >> 4) | ((uint64_t)(lbo >> 4) << 16) | ((uint64_t)(sbo >> 4) << 32) | ((uint64_t)swz << 62);
}
#define WG_FENCE() asm volatile("wgmma.fence.sync.aligned;" ::: "memory")
#define WG_COMMIT() asm volatile("wgmma.commit_group.sync.aligned;" ::: "memory")
#define WG_WAIT(n) asm volatile("wgmma.wait_group.sync.aligned " #n ";" ::: "memory")
__device__ __forceinline__ uint32_t lds32(uint32_t a) { uint32_t v; asm volatile("ld.shared.u32 %0, [%1];" : "=r"(v) : "r"(a) : "memory"); return v; }
__device__ __forceinline__ uint2 lds64(uint32_t a) { uint2 v; asm volatile("ld.shared.v2.u32 {%0,%1}, [%2];" : "=r"(v.x), "=r"(v.y) : "r"(a) : "memory"); return v; }
__device__ __forceinline__ uint4 lds128(uint32_t a) { uint4 v; asm volatile("ld.shared.v4.u32 {%0,%1,%2,%3}, [%4];" : "=r"(v.x), "=r"(v.y), "=r"(v.z), "=r"(v.w) : "r"(a) : "memory"); return v; }
__device__ __forceinline__ float4 lds128f(uint32_t a) { float4 v; asm volatile("ld.shared.v4.f32 {%0,%1,%2,%3}, [%4];" : "=f"(v.x), "=f"(v.y), "=f"(v.z), "=f"(v.w) : "r"(a) : "memory"); return v; }
__device__ __forceinline__ void sts32(uint32_t a, uint32_t v) { asm volatile("st.shared.u32 [%0], %1;" ::"r"(a), "r"(v) : "memory"); }
__device__ __forceinline__ void sts64(uint32_t a, uint32_t x, uint32_t y) { asm volatile("st.shared.v2.u32 [%0], {%1,%2};" ::"r"(a), "r"(x), "r"(y) : "memory"); }
__device__ __forceinline__ void sts128(uint32_t a, uint4 v) { asm volatile("st.shared.v4.u32 [%0], {%1,%2,%3,%4};" ::"r"(a), "r"(v.x), "r"(v.y), "r"(v.z), "r"(v.w) : "memory"); }
__device__ __forceinline__ void stsm4(uint32_t a, uint32_t r0, uint32_t r1, uint32_t r2, uint32_t r3) {
  asm volatile("stmatrix.sync.aligned.m8n8.x4.shared.b16 [%0], {%1,%2,%3,%4};" ::"r"(a), "r"(r0), "r"(r1), "r"(r2), "r"(r3) : "memory");
}
__device__ __forceinline__ void stsm4t(uint32_t a, uint32_t r0, uint32_t r1, uint32_t r2, uint32_t r3) {
  asm volatile("stmatrix.sync.aligned.m8n8.x4.trans.shared.b16 [%0], {%1,%2,%3,%4};" ::"r"(a), "r"(r0), "r"(r1), "r"(r2), "r"(r3) : "memory");
}
__device__ __forceinline__ void ldsm4(uint32_t a, uint32_t& r0, uint32_t& r1, uint32_t& r2, uint32_t& r3) {
  asm volatile("ldmatrix.sync.aligned.m8n8.x4.shared.b16 {%0,%1,%2,%3}, [%4];" : "=r"(r0), "=r"(r1), "=r"(r2), "=r"(r3) : "r"(a) : "memory");
}
__device__ __forceinline__ void ldsm4t(uint32_t a, uint32_t& r0, uint32_t& r1, uint32_t& r2, uint32_t& r3) {
  asm volatile("ldmatrix.sync.aligned.m8n8.x4.trans.shared.b16 {%0,%1,%2,%3}, [%4];" : "=r"(r0), "=r"(r1), "=r"(r2), "=r"(r3) : "r"(a) : "memory");
}
__device__ __forceinline__ void hmma(float* d, uint32_t a0, uint32_t a1, uint32_t a2, uint32_t a3, uint32_t b0, uint32_t b1) {
  asm volatile("mma.sync.aligned.m16n8k16.row.col.f32.bf16.bf16.f32 {%0,%1,%2,%3}, {%4,%5,%6,%7}, {%8,%9}, {%0,%1,%2,%3};"
               : "+f"(d[0]), "+f"(d[1]), "+f"(d[2]), "+f"(d[3]) : "r"(a0), "r"(a1), "r"(a2), "r"(a3), "r"(b0), "r"(b1));
}
__device__ __forceinline__ void lds32_if(bool on, uint32_t& v, uint32_t a) {
  asm volatile("{\n.reg .pred p;\nsetp.ne.b32 p, %2, 0;\n@p ld.shared.u32 %0, [%1];\n}" : "=r"(v) : "r"(a), "r"((int)on) : "memory");
}
__device__ __forceinline__ void st_peer(uint32_t ra, uint4 v, uint32_t rbar) {
  asm volatile("st.async.weak.shared::cluster.mbarrier::complete_tx::bytes.v4.b32 [%0], {%1,%2,%3,%4}, [%5];" ::"r"(ra), "r"(v.x), "r"(v.y), "r"(v.z), "r"(v.w), "r"(rbar) : "memory");
}
__device__ __forceinline__ void st_peer4(uint32_t ra, const uint4* v, uint32_t rbar) {
#define SP(o, a, b, c, d) "st.async.weak.shared::cluster.mbarrier::complete_tx::bytes.v4.b32 [%0+" #o "], {%" #a ",%" #b ",%" #c ",%" #d "}, [%1];\n"
  asm volatile(SP(0, 2, 3, 4, 5) SP(512, 6, 7, 8, 9) SP(1024, 10, 11, 12, 13) SP(1536, 14, 15, 16, 17)
               ::"r"(ra), "r"(rbar), "r"(v[0].x), "r"(v[0].y), "r"(v[0].z), "r"(v[0].w), "r"(v[1].x), "r"(v[1].y), "r"(v[1].z), "r"(v[1].w),
                 "r"(v[2].x), "r"(v[2].y), "r"(v[2].z), "r"(v[2].w), "r"(v[3].x), "r"(v[3].y), "r"(v[3].z), "r"(v[3].w) : "memory");
}
__device__ __forceinline__ uint32_t ldg32(const void* p) { uint32_t v; asm volatile("ld.global.nc.u32 %0, [%1];" : "=r"(v) : "l"(p)); return v; }
__device__ __forceinline__ uint32_t ldg16(const void* p) { uint16_t v; asm volatile("ld.global.nc.u16 %0, [%1];" : "=h"(v) : "l"(p)); return v; }
__device__ __forceinline__ uint32_t pack2(float lo, float hi) { uint32_t d; asm("cvt.rn.bf16x2.f32 %0, %1, %2;" : "=r"(d) : "f"(hi), "f"(lo)); return d; }
__device__ __forceinline__ float blo(uint32_t x) { return __uint_as_float(x << 16); }
__device__ __forceinline__ float bhi(uint32_t x) { return __uint_as_float(x & 0xffff0000u); }
__device__ __forceinline__ float bround(float x) { return bhi(pack2(0.f, x)); }
__device__ __forceinline__ uint32_t bmul2(uint32_t a, uint32_t b) { uint32_t d; asm("mul.rn.bf16x2 %0, %1, %2;" : "=r"(d) : "r"(a), "r"(b)); return d; }
__device__ __forceinline__ uint32_t badd2(uint32_t a, uint32_t b) { uint32_t d; asm("add.rn.bf16x2 %0, %1, %2;" : "=r"(d) : "r"(a), "r"(b)); return d; }
__device__ __forceinline__ uint32_t bfma2(uint32_t a, uint32_t b, uint32_t c) { uint32_t d; asm("fma.rn.bf16x2 %0, %1, %2, %3;" : "=r"(d) : "r"(a), "r"(b), "r"(c)); return d; }
__device__ __forceinline__ float silu(float x) { return __fdividef(x, 1.f + __expf(-x)); }
__device__ __forceinline__ float gelu2(float a, float k1, float k2) {
  float u, t;
  asm volatile("mul.rn.f32 %0, %1, %1;" : "=f"(u) : "f"(a));
  asm("tanh.approx.f32 %0, %1;" : "=f"(t) : "f"(a * fmaf(u, k2, k1)));
  asm volatile("fma.rn.f32 %0, %0, %1, %0;" : "+f"(a) : "f"(t));
  return a;
}
__device__ __forceinline__ void stage_end() { asm volatile("pmevent 1;"); }
__device__ __forceinline__ uint32_t baffine(uint32_t x, uint32_t c) {
  uint32_t d;
  asm("{\n.reg .b16 l, h;\n.reg .b32 a, b;\nmov.b32 {l, h}, %2;\nmov.b32 a, {l, l};\nmov.b32 b, {h, h};\nfma.rn.bf16x2 %0, %1, a, b;\n}" : "=r"(d) : "r"(x), "r"(c));
  return d;
}
__device__ __forceinline__ uint32_t clk32() { uint32_t t; asm volatile("mov.u32 %0, %%clock;" : "=r"(t)::"memory"); return t; }
__device__ __forceinline__ void sleep_until(uint32_t t0) {
#pragma unroll 1
  while (__any_sync(0xffffffffu, (int)(clk32() - t0) < 0)) __nanosleep(20);
}

#define TSX(mask, id) do {} while (0)
#define TGX(id) do {} while (0)
#define FX(id) do {} while (0)
#define TS1(id) TSX(1, id)
#define TS2(id) TSX(2, id)
#define TS3(id) TSX(4, id)
#define TSS(id) TSX(7, id)
#define W0(id) (w == 0 ? (id) : 127)

template <int N>
__device__ __forceinline__ void bfly(float* v, int lane, int mask) {
  const bool b = lane & mask;
#pragma unroll
  for (int i = 0; i < N / 2; i++) {
    float mine = b ? v[i + N / 2] : v[i], other = b ? v[i] : v[i + N / 2];
    v[i] = mine + __shfl_xor_sync(0xffffffffu, other, mask);
  }
}
__device__ __forceinline__ float quad_sum(float x) { x += __shfl_xor_sync(0xffffffffu, x, 1); return x + __shfl_xor_sync(0xffffffffu, x, 2); }

template <int N>
__device__ __forceinline__ void conv_tri(float* acc, uint32_t (*A)[4], uint64_t db) {
  if constexpr (N == 128) wrs128_first(acc, A[0], db); else WRS<N>::mma(acc, A[0], db);
  if constexpr (N > 16) conv_tri<N - 16>(acc, A + 1, db + 16);
}
__device__ __forceinline__ void conv_mma(float* acc, uint32_t (*A)[4], uint64_t db) {
  WG_FENCE();
  conv_tri<128>(acc, A + 8, db + 128);
  WG_COMMIT();
  WG_FENCE();
  WRS<128>::mma(acc, A[7], db + 112); WRS<128>::mma(acc, A[6], db + 96);
  WG_COMMIT();
  WG_WAIT(1);
  WG_FENCE();
  conv_tri<128>(acc + 64, A, db + 128);
#pragma unroll
  for (int T = 5; T >= 0; T--) WRS<128>::mma(acc, A[T], db + 16 * T);
  WG_COMMIT();
}
template <int N>
__device__ __forceinline__ void zero_acc(float* a) {
#pragma unroll
  for (int i = 0; i < N; i += 2) asm volatile("mov.b64 {%0, %1}, 0;" : "=f"(a[i]), "=f"(a[i + 1]));
}
template <int N>
__device__ __forceinline__ void undef(float* a) {
#pragma unroll
  for (int i = 0; i < N; i++) asm volatile("" : "=f"(a[i]));
}
template <int N>
__device__ __forceinline__ void undef(uint32_t* a) {
#pragma unroll
  for (int i = 0; i < N; i++) asm volatile("" : "=r"(a[i]));
}
__device__ __forceinline__ uint32_t ext_frag(float mu, float sg, int q) {
  const float mh = bround(-mu), sh = bround(sg);
  const float lo = q == 0 ? mh : q == 1 ? -mu - mh : sh, hi = q == 0 ? mh : q == 1 ? sh : sg - sh;
  return pack2(lo, hi) & (q == 3 ? 0u : ~0u);
}
__device__ __forceinline__ uint32_t opaque(uint32_t x) { asm volatile("" : "+r"(x)); return __shfl_sync(0xffffffffu, x, 0); }
__device__ __forceinline__ uint32_t tagw(uint32_t x, uint32_t par) { return (x & ~1u) | par; }
__device__ __forceinline__ uint32_t bitsel(uint32_t x, uint32_t y, uint32_t mask) { return (x & ~mask) | (y & mask); }
__device__ __forceinline__ uint32_t stale(uint32_t acc, uint32_t x, uint32_t par) { uint32_t d; asm("lop3.b32 %0, %1, %2, %3, 0xf6;" : "=r"(d) : "r"(acc), "r"(x), "r"(par)); return d; }
__device__ __forceinline__ uint32_t stale4(uint32_t acc, uint4 a, uint32_t par) { return stale(stale(stale(stale(acc, a.x, par), a.y, par), a.z, par), a.w, par); }
__device__ __forceinline__ bool any_stale(uint32_t acc) { return __builtin_expect(__any_sync(0xffffffffu, acc & 1), 0); }
__device__ __forceinline__ float sum2(uint32_t a, uint32_t b) { return bround(__uint_as_float(a) + __uint_as_float(b)); }
__device__ __forceinline__ void refetch(uint32_t ta, const uint4* gp, uint32_t wo, uint32_t par) {
#pragma unroll 1
  while (any_stale(lds32(ta + wo) ^ par)) { sts128(ta, ld_relaxed4(gp)); sts128(ta + 16, ld_relaxed4(gp + 1)); }
  fence_async_s();
}

__global__ void __cluster_dims__(2, 1, 1) __launch_bounds__(512, 1)
fused_kernel(const __grid_constant__ Params p, const __grid_constant__ Maps tm) {
  extern __shared__ __align__(1024) unsigned char smem_raw[];
  const uint32_t tstart = __shfl_sync(0xffffffffu, clk32() + (threadIdx.x & 31), 0);
  const uint32_t sb = __shfl_sync(0xffffffffu, (uint32_t)__cvta_generic_to_shared(smem_raw), 0);
  const int tid = threadIdx.x, lane = tid & 31;
  const int warp = __shfl_sync(0xffffffffu, tid >> 5, 0);
  const int wg = warp >> 2, w = warp & 3, t128 = tid & 127;
  const int r = lane >> 2, q = lane & 3, mi = lane >> 3, rr = lane & 7;
  Scratch* const G = p.g;
  auto BAR = [&](int i) { return sb + SM_BAR + i * 8; };
  unsigned cnt0 = 0;
  if (warp == 15) cnt0 = ld_relaxed(G->cnt + min(lane, C_E + 1) * 32);
  unsigned crank, mytpc;
  asm("mov.u32 %0, %%smid;" : "=r"(mytpc));
  asm("mov.u32 %0, %%cluster_ctarank;" : "=r"(crank));
  mytpc = (p.by_sm ? mytpc : blockIdx.x) >> 1;
  const int bid = (mytpc < 60 ? mytpc : mytpc < 62 ? mytpc + 4 : mytpc - 2) * 2 + crank;
  if ((warp >> 1) == 5 && bid < 128) asm volatile("prefetch.global.L2 [%0];" ::"l"((warp == 10 ? p.k : p.v) + ((bid >> 1) * 32 + lane) * 640 + crank * 64));
  if (wg == 1) asm volatile(ELECT "prefetch.tensormap [%0];\n}" ::"l"(&tm.k + w) : "memory");
#define BI(o) "@e mbarrier.init.shared::cta.b64 [%0+" #o "], %1;\n"
  if (warp == 12 && bid < 128) {
    asm volatile("{\n.reg .pred e;\nelect.sync _|e, 0xffffffff;\n" BI(0) "fence.mbarrier_init.release.cluster;\n}" ::"r"(BAR(B_KV)), "r"(1) : "memory");
    w_expect(BAR(B_KV), 11520 + 5120);
    tma5d(sb, &tm.k, crank * 64, 0, (bid >> 1) * 4 - 1, 0, BAR(B_KV));
    tma5d(sb + KV_V, &tm.v, crank * 64, 0, (bid >> 1) * 4, 0, BAR(B_KV));
    bulk_g2s(sb + SM_S, p.shiftk, 5120, BAR(B_KV));
  }
  if (warp < 4) {
#pragma unroll 1
    for (int g = warp; g < 16; g += 4)
      asm volatile("{\n.reg .pred e;\nelect.sync _|e, 0xffffffff;\n" BI(8) BI(16) BI(24) BI(32) BI(40) BI(48) BI(56) "fence.mbarrier_init.release.cluster;\n}"
                   ::"r"(BAR(g * 7)), "r"(g < 7 ? (bid >= 128 && !g ? 14 : 1) : g < 9 ? 2 : 4) : "memory");
  }
  if (tid == 96) sts32(sb + SM_TPC, mytpc);
  asm volatile("barrier.cluster.arrive.relaxed.aligned;" ::: "memory");
  auto READY = [&]() { asm volatile("barrier.cluster.wait.aligned;" ::: "memory"); };
  auto EPOCH = [&]() { mbar_wait(BAR(B_EP), 0); return lds32(sb + SM_TPC + 4); };
  auto SET_EPOCH = [&]() { const unsigned e = __reduce_min_sync(0xffffffffu, cnt0 >> 6) + 1u; sts32(sb + SM_TPC + 4, e); w_arrive(BAR(B_EP)); return e; };

  if (bid >= 128) {
    const int j = bid - 128;
    READY();
    constexpr uint32_t S_TAB = SM_S;
    if (warp < 14) {
      const unsigned tag = EPOCH(), par = tag & 1;
      const uint32_t to = sb + S_TAB + (tid >> 2) * 64 + (tid & 1) * 16 + (tid & 2) * 2;
      st_relaxed4(G->vt + (tid < 224 ? j * 224 : (3 + j) * 224) + tid, make_uint4(0, 0, 0, (tag - 1) & 0x3fff));
      if (tid < 192 && j * 192 + tid < 640) st_relaxed(G->gb + j * 192 + tid, par ^ 1);
      if (tid < 160) {
        const uint32_t c0 = ldg32(p.c + tid * 4), c1 = ldg32(p.c + tid * 4 + 2);
        sts32(to + 4096, pack2(silu(blo(c0)), silu(bhi(c0)))); sts32(to + 4104, pack2(silu(blo(c1)), silu(bhi(c1))));
        sleep_until(tstart + T_SPARE - 1000);
        wait_cnt_b(G, C_M + (lane & 1), tag * 64u);
        __syncwarp();
        const uint4* mp = (const uint4*)(G->modp + 1920) + tid;
        uint4 a, b, c, d;
        int spin = 0;
#pragma unroll 1
        do {
          a = ld_relaxed4(mp); b = ld_relaxed4(mp + 800); c = ld_relaxed4(mp + 160); d = ld_relaxed4(mp + 960);
          if (++spin > (1 << 19)) __trap();
        } while (any_stale(stale4(stale4(stale4(stale4(0, a, par), b, par), c, par), d, par)));
        sts32(to, pack2(1.f + sum2(c.x, d.x), 1.f + sum2(c.y, d.y))); sts32(to + 8, pack2(1.f + sum2(c.z, d.z), 1.f + sum2(c.w, d.w)));
        sts32(to + 32, pack2(sum2(a.x, b.x), sum2(a.y, b.y))); sts32(to + 40, pack2(sum2(a.z, b.z), sum2(a.w, b.w)));
      }
      bar_sync(1, 448);
      TSS(warp == 0 ? 10 : 127);
            int st = 0, ph = 0;
#pragma unroll 1
      for (int part = 0; part < 3; part++) {
        float d[2][4] = {{0.f, 0.f, 0.f, 0.f}, {0.f, 0.f, 0.f, 0.f}};
        const int ch = 2 * warp + (mi & 1) + (part < 2 && part == (j == 1) ? 4 : 0);
        const uint32_t ao = sb + (ch >> 3) * 8192 + (rr + (mi >> 1) * 8) * 128 + (((ch & 7) ^ rr) << 4);
#pragma unroll 1
        for (int u = 0; u < 10; u++) {
          uint32_t a[4][4];
          uint2 b[4];
#pragma unroll
          for (int i = 0; i < 4; i++) b[i] = lds64(sb + S_TAB + (part >> 1) * 4096 + (u * 4 + i) * 64 + (r & 1) * 32 + q * 8);
          mbar_wait(BAR(B_FULL1 + st), ph);
#pragma unroll
          for (int i = 0; i < 4; i++) ldsm4t(ao + st * 32768 + i * 2048, a[i][0], a[i][1], a[i][2], a[i][3]);
#pragma unroll
          for (int i = 0; i < 4; i++) hmma(d[i & 1], a[i][0], a[i][1], a[i][2], a[i][3], b[i].x, b[i].y);
          w_arrive(BAR(1 + st));
          if (++st == 6) { st = 0; ph ^= 1; }
        }
#pragma unroll
        for (int i = 0; i < 2; i++) {
          const float a = d[0][2 * i] + d[1][2 * i], b = d[0][2 * i + 1] + d[1][2 * i + 1], ah = bround(a), bh = bround(b);
          const int cc = warp * 16 + i * 8 + r;
          if (q == 0 && part < 2) st_relaxed4(G->vt + (part * 4 + j) * 224 + cc, make_uint4(pack2(ah, a - ah), pack2(ah, bh), pack2(b - bh, bh), tag & 0x3fff));
          if (q == 0 && part == 2 && cc < 192 && j * 192 + cc < 640) st_relaxed(G->gb + j * 192 + cc, __float_as_uint(ah) | par);
        }
        TSS(warp == 0 ? 1 + part : 127);
      }
    } else {
      const int x = warp - 14;
      if (x) SET_EPOCH();
      if (lane == 0) { tmap_prefetch(x ? &tm.w2 : &tm.wm); }
      sleep_until(tstart + T_SPARE);
      int st = 0, ph = 1;
#pragma unroll 1
      for (int u = 0; u < 30; u++) {
        const int part = u / 10, row = (u - part * 10) * 64, base = (part ? 0 : 864) + nstart(j);
        const uint32_t fb = BAR(B_FULL1 + st), dst = sb + st * 32768;
        mbar_wait_b(BAR(1 + st), ph);
        if (part == 2) {
          w_expect(fb, x ? 8192 : 16384);
          tma5d(dst + x * 16384, &tm.wm, min(3200 + j * 192 + x * 128, 3776), row, 0, 0, fb);
          if (!x) tma5d(dst + 8192, &tm.wm, min(3264 + j * 192, 3776), row, 0, 0, fb);
        } else { w_expect(fb, 16384); tma3d(dst + x * 16384, &tm.w2, (base & ~63) + x * 128, row, 0, fb); }
        if (++st == 6) { st = 0; ph ^= 1; }
      }
    }
    return;
  }
  const int m = p.tile[bid >> 1] >> 1, n = (p.tile[bid >> 1] & 1) * 2 + crank;
  const uint32_t peer = mapa(sb, crank ^ 1) - sb;

  unsigned tag = 0, par = 0;
  if (wg == 3) {
    asm volatile("setmaxnreg.dec.sync.aligned.u32 24;");
    auto pf_wsp = [&](int i) {
      const __nv_bfloat16* a = p.wsp + ((m >> 1) * 128 + (m & 1) * 32 + lane) * 2048 + ((i + ROT * (m >> 3)) & 15) * 128 + (i >> 4) * 64;
      asm volatile("prefetch.global.L2 [%0];\nprefetch.global.L2 [%0+262144];" ::"l"(a));
    };
    if (w < 3) {
      {
        const int it = (int)(((lane < 8 ? SEQ0 : lane < 16 ? SEQ1 : lane < 24 ? SEQ2 : SEQ3) >> (8 * rr)) & 255), ty = it >> 4, s = it & 15;
        const bool on = lane < 25 && (ty != 3 || bid < 100);
        const uint32_t bi = max(ty - 1, 0) * 5 + s;
        const uint32_t a0 = ty == 3 ? (bid >> 1) * 64 + ((crank * 320 + s * 64) << 16) : ty == 2 ? 0 : s * 128 + crank * 64;
        const uint32_t a1 = ty < 2 ? ((bid >> 1) * 4 - 1 + ty) << 8 : ty == 2 ? (s * 128 + bid) << 8 : ty == 3 ? 0 : ((m & ~1) << 8) + (m & 1) * 4;
        const uint32_t a2 = (ty == 2 ? offF(s) + 16 : s * 16384 + (ty < 2 ? ty * KV_V : ((ty ^ crank) & 1) * 8192)) + ty + (bi << 18) + ((ty > 2 ? B_KVF + s : B_EP) << 24);
        const uint32_t a3 = tstart + T_2 - 2 * PACE_D + lane * PACE_D + min(max(lane - 15, 0), 5) * (PACE_W - PACE_D) + max(lane - 20, 0) * (PACE_Q - PACE_D);
        unsigned todo = __ballot_sync(0xffffffffu, on) & (0x49249249u << (2 + w));
        READY();
        if (on && ty != 1 && lane && !w) mbar_expect(BAR(bi), ty == 0 ? 11520 : ty == 2 ? 4096 : 8192);
#pragma unroll 1
        while (todo) {
          const int i = __ffs(todo) - 1;
          const uint32_t b0 = __shfl_sync(0xffffffffu, a0, i), b1 = __shfl_sync(0xffffffffu, a1, i), b2 = __shfl_sync(0xffffffffu, a2, i);
          todo &= todo - 1;
          sleep_until(__shfl_sync(0xffffffffu, a3, i));
          if (i < 6) TS1(94 + i);
          if ((b2 & 7) > 2) mbar_wait_b(BAR(b2 >> 24), 0);
          tma5d(sb + (b2 & 0x3ff80), &tm.k + (b2 & 7), b0 & 0xffff, b0 >> 16, (int)b1 >> 8, b1 & 255, BAR((b2 >> 18) & 63));
        }
      }
      TS1(w == 1 ? 95 : 127);
    }
    if (w == 1 || w == 2) {
      const int x = w - 1;
      if (STOP_AFTER >= 2) {
        sleep_until(tstart + T_WIN);
#pragma unroll 1
        for (int g = 0; g < 20; g++) {
          const int base = (g < 10 ? 864 : 0) + nstart(n), row = ((g < 10 ? g : g - 10) ^ crank) * 64;
          const uint32_t fb = BAR(B_FULL1 + (g & 3)), dst = sb + SM_R + (g & 3) * 32768;
          mbar_wait(fb + (B_EMPTY1 - B_FULL1) * 8, (g >> 2) & 1);
          w_expect(fb, 16384); tma3d(dst + x * 16384, &tm.w2, (base & ~63) + x * 128, row, 0, fb);
        }
      }
      if (STOP_AFTER >= 3) {
        if (x) {
          const unsigned tag = lds32(sb + SM_TPC + 4);
#pragma unroll 1
          for (int h = 0; h < 2; h++) {
            pf_wsp(20 + 4 * h + n);
            mbar_wait(BAR(B_LF), h);
#pragma unroll 1
            while (__any_sync(0xffffffffu, (int)(ld_acquire(G->flagL + (n * 32 + lane) * 8) - 2 * tag - h) < 0)) {}
            if (PFENCE) fence_async_g();
            w_arrive(BAR(B_LOK));
            TS2(91 + h);
          }
          pf_wsp(28 + n);
          if (lane == 0) asm volatile("cp.async.bulk.prefetch.L2.global [%0], 8640;" ::"l"(p.wout + bid * 4320) : "memory");
          mbar_wait(BAR(B_ACK), 0);
        } else {
          int st = 0, ph = 0;
          mbar_wait(BAR(B_X1D), 0);
#pragma unroll 1
          for (int i = 0; i < 32; i++) {
            const uint32_t fb = BAR(B_FULL2 + st);
            mbar_wait(fb + (B_EMPTY2 - B_FULL2) * 8, ph);
            w_expect(fb, 8192); tma_rows(sb + placeA(st), &tm.wsp, ((i + ROT * (m >> 3)) & 15) * 128 + (i >> 4) * 64, m & ~1, (m & 1) * 4, fb);
            if (++st == 5) { st = 0; ph ^= 1; }
          }
          w_arrive(BAR(B_ACK));
        }
      }
      if (STOP_AFTER >= 4) {
#pragma unroll 1
        for (int k = 0; k < 10; k++) {
          const int st = 1 + ((k + 1) & 3);
          const uint32_t fb = BAR(B_FULL2 + st);
          mbar_wait(fb + (B_EMPTY2 - B_FULL2) * 8, ((k + 1) >> 2) & 1);
          TS3(x ? 127 : 60 + k);
          w_expect(fb, 14336);
          tma2d(sb + placeB(st) + x * 14336, &tm.wo, (k < 8 ? (k & 2) + x : 4) * 128 + crank * 64, nstart(n ^ (k < 8 ? k >> 2 : k & 1)) + 112 * (k < 8 ? k & 1 : x), fb);
        }
      }
    } else if (w == 3) {
      READY();
      TS1(103);
      const unsigned tag = SET_EPOCH();
      TS1(100);
      if (lane < 8) st_relaxed(G->flagL + (n * 32 + m) * 8 + lane, 2 * tag - 1);
      if (lane < 9) mbar_expect(BAR(B_AP + lane), lane < 5 ? 8192 : lane < 7 ? 2048 : 14336);
      mbar_wait(BAR(B_KV), 0);
#pragma unroll 1
      for (int s = 0; s < 5; s++) {
        if (s && lane < 2) tmap_prefetch(&tm.wm + 2 * s - 2 + lane);
#pragma unroll 1
        while (__any_sync(0xffffffffu, (int)(ld_relaxed(G->cnt + (C_A + 2 * s + (bid >> 6)) * 32) - tag * 64u) < 0)) {}
        w_expect(BAR(B_U + s), 4096); bulk_g2s(sb + offU(s), G->T + (s * 128 + bid) * 256, 4096, BAR(B_U + s));
        TS1(80 + s);
      }
      {
        uint32_t t;
        asm volatile("ld.shared::cluster.u32 %0, [%1];" : "=r"(t) : "r"(sb + SM_TPC + peer) : "memory");
        if (t != mytpc) __trap();
        unsigned todo = 127;
        if (lane < 5) mbar_expect(BAR(B_YH + lane), 8192);
        mbar_wait(BAR(B_WMF), 0);
#pragma unroll 1
        do {
          unsigned rdy = __ballot_sync(0xffffffffu, ((todo >> lane) & 1) && (int)(ld_relaxed(G->cnt + (lane < 5 ? C_Y + 2 * lane + crank : C_M - 5 + lane) * 32) - tag * 64u) >= 0);
          todo &= ~rdy;
          if ((rdy & 96) && todo < 32) { w_arrive(BAR(B_YH + 5)); TS1(90); }
#pragma unroll 1
          for (rdy &= 31; rdy; rdy &= rdy - 1) {
            const int s = __ffs(rdy) - 1;
            tma3d(sb + s * 16384 + (crank ^ 1) * 8192, &tm.y, 0, s * 128 + crank * 64, m * 2, BAR(B_YH + s));
            TS1(85 + s);
          }
        } while (todo);
      }
#pragma unroll 1
      for (int part = 0; part < 2; part++) {
        const uint4* vp = G->vt + (part * 4 + n) * 224;
        if (STOP_AFTER >= 2) mbar_wait2(BAR(part ? B_VTF : B_AO), BAR(B_AO + 1), 0, 0);
#pragma unroll 1
        while (__any_sync(0xffffffffu, ld_relaxed(&vp[223].w) != (tag & 0x3fff))) {}
        unsigned bad, ph = 1;
#pragma unroll 1
        do {
          w_expect(BAR(B_U + part), 3584); bulk_g2s(sb + (STOP_AFTER >= 2 ? SM_VT : SM_X1), vp, 3584, BAR(B_U + part));
          mbar_wait(BAR(B_U + part), ph);
          ph ^= 1; bad = 0;
#pragma unroll
          for (int k = 0; k < 7; k++) bad |= lds32(sb + (STOP_AFTER >= 2 ? SM_VT : SM_X1) + k * 512 + lane * 16 + 12) ^ tag;
        } while (__any_sync(0xffffffffu, bad & 0x3fff));
        w_arrive(BAR(B_VT));
        TS2(75 + part);
      }
      w_count(G, C_E + crank);
      if (STOP_AFTER >= 2) {
#pragma unroll 1
        for (int h = 0; h < 2; h++) {
          mbar_wait2(BAR(B_PUB), BAR(B_X1D), h, 0);
          fence_async_g();
          fence_gpu();
          if (lane < 8) st_relaxed(G->flagL + (n * 32 + m) * 8 + lane, 2 * tag + h);
          w_arrive(BAR(B_LF));
          TS2(77 + h);
        }
      }
      if (STOP_AFTER >= 4) {
#pragma unroll 1
        while (__any_sync(0xffffffffu, ld_acquire(G->flagL + ((n ^ 2) * 32 + m) * 8) != 2 * tag + 1)) __nanosleep(200);
        fence_async_g();
#pragma unroll 1
        for (int s = 0; s < 5; s++) {
          uint2 a;
#pragma unroll 1
          for (;;) { a = ld_relaxed2(G->gb + s * 128 + crank * 64 + lane * 2); if (!any_stale(stale(a.x ^ tag, a.y, tag))) break; __nanosleep(200); }
          sts64(sb + SM_GB + s * 256 + mi * 64 + q * 16 + (r & 1) * 8, a.x & ~1u, a.y & ~1u);
        }
        w_arrive(BAR(B_GB));
      }
    } else {
      if (STOP_AFTER >= 2) {
#pragma unroll 1
        for (int s = 0; s < 5; s++) {
          const uint32_t own = sb + s * 16384 + crank * 8192;
          if (BULK_A) {
            mbar_wait_b(BAR(B_RF + s), 0);
            mbar_wait_b(BAR(B_AO + s), 0);
            bulk_s2peer(own + peer, own, 8192, BAR(B_AP + s) + peer);
          }
          mbar_wait_b(BAR(B_XS + s), 0);
          tma5d_store(&tm.x1, s * 128 + crank * 64, m & ~1, (m & 1) * 4 + (n & 2), sb + SM_X1 + (s & 1) * 4096);
          bulk_commit();
          pf_wsp(4 * s + n);
          asm volatile("cp.async.bulk.wait_group 0;" ::: "memory");
          w_arrive(BAR(s < 4 ? B_XF + (s & 1) : B_X1D));
        }
      }
      if (STOP_AFTER >= 3) {
        const unsigned tag = lds32(sb + SM_TPC + 4);
        unsigned early = 0;
        int st = 0, ph = 0, spin = 0;
        const unsigned* fp = G->flagE + n * 1024 + rr * 8;
        mbar_wait_b(BAR(B_PUB), 0);
        if (POLL0) sleep_until(clk32() + POLL0);
        TS2(100);
#pragma unroll 1
        for (int i = 0; i < 32; i++) {
          const int M = (i + ROT * (m >> 3)) & 15;
          const uint32_t fb = BAR(B_FULL2 + st);
          if (i < 4) {
            early >>= 8;
#pragma unroll 1
            while (~early & 255) {
              const unsigned a = ld_relaxed(fp + ((M + min(mi, 3 - i)) & 15) * 64), b = ld_relaxed(fp + ((M + (mi < 3 - i ? mi : 4 - i)) & 15) * 64);
              early = __ballot_sync(0xffffffffu, a == tag && b == tag);
              if (++spin > (1 << 19)) __trap();
              if (spin < 3) TS2(100 + spin);
            }
          }
          if (i == 16) TS2(103);
          if (i == 5 || i == 16) mbar_wait_b(BAR(B_LOK), i >> 4);
          mbar_wait_b(fb + (B_EMPTY2 - B_FULL2) * 8, ph);
          if (i < 10 || i == 16) TS2(min(80 + i, 90));
          w_expect(fb, 28672); bulk_g2s(sb + placeB(st), G->z2n + (n * 32 + (i & 16) + M) * IMG, 28672, fb);
          if (++st == 5) { st = 0; ph ^= 1; }
        }
      }
      w_arrive(BAR(B_DONE + 3));
#pragma unroll 1
      for (int i = 3; i >= 0; i--) mbar_wait_b(BAR(B_DONE + i), 0);
      return;
    }
    goto done;
  }
  if (wg < 2) {
    {
      const int i = min(warp ^ 4, NPF), it = (int)((SEQ0 >> 16 | SEQ1 << 48) >> (8 * i)) & 255, s = it & 15;
      const __nv_bfloat16* a = it >= 32 ? p.ssmk + (s * 128 + bid) * 2048 + lane * 64 : (it >= 16 ? p.v : p.k) + ((bid >> 1) * 32 + lane) * 640 + s * 128 + crank * 64;
      sleep_until(tstart + T_2 + i * PACE_D);
      if (i < NPF) asm volatile("prefetch.global.L2 [%0];" ::"l"(a));
    }
    asm volatile("setmaxnreg.inc.sync.aligned.u32 192;");
    READY();
    tag = EPOCH(); par = tag & 1;
    {
      const uint32_t lofs = (r & 1) ? (16 + 4 * (4 * w + ((r - 1) >> 1) - q)) : (16 + 4160 + 4 * (4 * w + (r >> 1) - 1 - q));
      const uint32_t pl = sb + SM_R + (5 + 2 * wg) * 16384, pa = pl + w * 4096 + ((255 - lane) ^ ((~lane & 8) >> 1)) * 16;
      uint32_t pg[4];
#pragma unroll
      for (int i = 0; i < 4; i++) { const uint32_t x = ((t128 & 112) + (lane & 1) * 8 + ((lane & 15) >> 1) - i) & 255; pg[i] = (x ^ ((x & 8) >> 1)) * 16; }
      if (lane < w) sts128(pa, make_uint4(0, 0, 0, 0));
      if (lane < 8 && 2 * w < 4 + wg) sts128(sb + offU(2 * w + 1 - wg) + 4096 + lane * 16, make_uint4(0, 0, 0, 0));
      fence_async_s();
      bar_sync(4 + wg, 128);
      if (!wg) {
        if (q < 2) st_relaxed2(G->st3 + ((m * 4 + n) * 2 + q) * 32 + w * 8 + r, par ^ 1, 0);
        if (lane < 8) st_relaxed(G->flagE + (n * 32 + m) * 32 + w * 8 + lane, tag - 1);
      }
      const uint32_t p0 = lane < w ? sb + SM_DUMMY + lane * 16 : pa, uo = t128 * 32 + r * 4;
      uint4* yp = G->Y + ((1 - wg) * 128 + bid) * 256 + t128;
      uint32_t A[16][4];
      auto frag = [&](bool on, uint32_t fa, int T) {
#pragma unroll
        for (int i = 0; i < 4; i++) lds32_if(on, A[T][i], fa + T * 256 + (i & 1) * 128 + (i & 2) * 32);
      };
      mbar_wait(BAR(B_FO + 1 - wg), 0);
#pragma unroll
      for (int T = 0; T < 16; T++) frag(true, sb + offF(1 - wg) + lofs, T);
#pragma unroll 1
      for (int s = 1 - wg;; s += 2) {
        float acc[128];
        const uint32_t ub = sb + offU(s), fa = sb + offF(s + 2) + lofs;
        mbar_wait(BAR(B_U + s), 0);
        const uint32_t ut = lds32(ub + uo);
        if (any_stale(ut ^ par)) { FX(118); refetch(ub + (uo & ~31), G->T + (s * 128 + bid) * 256 + (uo >> 5) * 2, uo & 31, par); }
        if (s) bar_sync(10 + wg, 256); else bar_sync(5, 128);
        TS1(W0(10 + s));
        conv_mma(acc, A, mkdesc(ub, 64, 128, 0));
        if (s < RDV0 || s > 3) bar_arrive(11 - wg, 256); else bar_sync(11 - wg, 256);
        mbar_wait(BAR(B_FO + min(s + 2, 4)), 0);
        WG_WAIT(0);
        TS1(W0(15 + s));
#pragma unroll
        for (int x = 7; x >= 0; x--) {
          frag(s < 3, fa, x);
          uint32_t pk[4];
#pragma unroll
          for (int i = 0; i < 4; i++) {
            const int jj = 4 * x + i;
            float lo = acc[4 * jj], hi = acc[4 * jj + 1];
            if (jj < 31) { lo += acc[4 * jj + 6]; hi += acc[4 * jj + 7]; }
            pk[i] = pack2(lo, hi);
          }
          stsm4t(x ? pa - x * 512 : p0, pk[0], pk[1], pk[2], pk[3]);
          if (CSTG) stage_end();
        }
        bar_sync(4 + wg, 128);
        TS1(W0(20 + s));
        uint4 v[8];
#pragma unroll
        for (int i = 0; i < 8; i++) v[i] = lds128(pl + (i & 3) * 4096 + (pg[i & 3] ^ ((i >> 2) * 2048)));
        auto finish = [&]() {
          if (w == 1) w_count(G, C_Y + 2 * s + (bid >> 6));
#pragma unroll
          for (int e = 0; e < 2; e++) {
            const uint4 a = v[4 * e], b = v[4 * e + 1], c = v[4 * e + 2], d = v[4 * e + 3];
            yp[e * 128] = make_uint4(tagw(badd2(badd2(a.x, b.x), badd2(c.x, d.x)), par), badd2(badd2(a.y, b.y), badd2(c.y, d.y)), badd2(badd2(a.z, b.z), badd2(c.z, d.z)), badd2(badd2(a.w, b.w), badd2(c.w, d.w)));
          }
          yp += 256 * 256;
          w_arrive(BAR(s > 0 ? B_EMPTY1 - 1 + s : B_NIL));
          TS1(W0(30 + s));
        };
        if (s >= 3) { finish(); break; }
#pragma unroll
        for (int T = 8; T < 16; T++) frag(true, fa, T);
        finish();
      }
    }
    if (!wg) {
      mbar_wait(BAR(B_YH + 5), 0);
      TS1(W0(61));
      if (w < 3) {
        const int t = min(t128, 64 + (t128 & 15));
        const uint4* mp = (const uint4*)G->modp + (t >> 4) * 32 + crank * 16 + (t & 15);
        uint4 v[8];
        uint32_t bad;
#pragma unroll 1
        do {
          bad = 0;
#pragma unroll
          for (int i = 0; i < 8; i++) v[i] = ld_relaxed4(mp + (i & 1) * 800 + ((i >> 1) + (i >= 6)) * 160);
#pragma unroll
          for (int i = 0; i < 8; i++) bad = stale4(bad, v[i], par);
        } while (any_stale(bad));
        const uint32_t o = sb + SM_MOD + (t >> 3) * 256 + (t & 1) * 128 + (t & 6) * 4;
#define MODE(f, k) { const float ga = sum2(v[4].f, v[5].f), cb = 1.f + sum2(v[6].f, v[7].f); sts64(o + k * 32, pack2(ga * bround(1.f + sum2(v[2].f, v[3].f)), ga * sum2(v[0].f, v[1].f)), pack2(cb, cb)); }
        MODE(x, 0); MODE(y, 1); MODE(z, 2); MODE(w, 3);
      }
      w_arrive(BAR(B_MT));
      TS1(W0(63));
      goto gemm;
    }
    asm volatile("setmaxnreg.dec.sync.aligned.u32 104;");
  } else {
    asm volatile("setmaxnreg.dec.sync.aligned.u32 104;");
    const uint32_t cv0 = ldg32(p.c + crank * 320 + min(t128, 79) * 4), cv1 = ldg32(p.c + crank * 320 + min(t128, 79) * 4 + 2);
    {
      uint32_t ad[8], mk[4];
#pragma unroll
      for (int x = 0; x < 8; x++) ad[x] = sb + q * 1280 + (((2 * w + (r >> 2)) ^ ((2 * q + x) & 7)) << 4) + (r & 3) * 4;
      const int pc = 255 - (bid >> 1) * 4 - q;
#pragma unroll
      for (int i = 0; i < 4; i++) mk[i] = ((pc >> 3) & 7) == (pc & 1) * 4 + i ? 0x10001u : 0u;
      uint4* d = G->T + (crank * 64 + (t128 >> 2) * 2) * 256 + pc;
      const uint32_t dsk = ldg16(p.ssmD + min(lane, 4) * 128 + bid);
      int sf = 0;
      TS1(W0(111));
      READY();
#pragma unroll 1
      for (int s = 0; s < 5; s++) {
        const uint32_t so = s * 16384;
        mbar_wait(BAR(B_KV + s), 0);
        TS1(W0(1 + s));
        if (HINT_A && s < HINT_A && w == 1) w_count(G, C_A + 2 * s + crank);
        const uint4 sk = lds128(sb + SM_S + (so >> 4) + crank * 512 + (t128 >> 2) * 16);
        uint32_t kk[11], o[8];
#pragma unroll
        for (int i = 0; i < 11; i++) kk[i] = i < 3 ? lds32(ad[i + 5] + so + (i + 5) * 128) : lds32(ad[(i - 1) & 7] + so + (i + 7) * 128);
#pragma unroll
        for (int i = 0; i < 8; i++) o[i] = lds32(ad[i] + so + KV_V + i * 128);
        const uint32_t w0 = __byte_perm(sk.x, sk.z, 0x5410), w1 = __byte_perm(sk.x, sk.z, 0x7632), w2 = __byte_perm(sk.y, sk.w, 0x5410), w3 = __byte_perm(sk.y, sk.w, 0x7632);
#pragma unroll
        for (int i = 0; i < 8; i++) o[i] = bmul2(bfma2(kk[i + 3], w0, bfma2(kk[i + 2], w1, bfma2(kk[i + 1], w2, bmul2(kk[i], w3)))), o[i]);
        if (s == 0) par = EPOCH() & 1;
#pragma unroll
        for (int i = 0; i < 4; i++) o[2 * i + 1] = bitsel(o[2 * i + 1], par * 0x10001u, mk[i]);
        d[s * 32768] = make_uint4(__byte_perm(o[1], o[0], 0x5410), __byte_perm(o[3], o[2], 0x5410), __byte_perm(o[5], o[4], 0x5410), __byte_perm(o[7], o[6], 0x5410));
        d[s * 32768 + 256] = make_uint4(__byte_perm(o[1], o[0], 0x7632), __byte_perm(o[3], o[2], 0x7632), __byte_perm(o[5], o[4], 0x7632), __byte_perm(o[7], o[6], 0x7632));
        {
          if (HINT_A < 5 && s >= HINT_A && w == 1) w_count(G, C_A + 2 * s + crank);
          w_arrive(BAR(B_KVF + s));
          TS1(W0(40 + s));
#pragma unroll 1
          for (; sf < ((HSEQ >> (4 * s)) & 15); sf++) {
            const uint32_t fE = sb + offF(sf) + 16 + t128 * 16, dk = __shfl_sync(0xffffffffu, dsk, sf);
            mbar_wait(BAR(B_F + sf), 0);
            TS1(W0(70 + sf));
            const uint4 e0 = lds128(fE), e1 = lds128(fE + 2048);
            const uint32_t n0 = lds32(fE + 16), n1 = lds32(fE + 2064), f0 = pack2(blo(e0.x) + blo(dk), bhi(e0.x));
            sts128(fE + 4160, make_uint4(__byte_perm(e0.x, e0.y, 0x5432), __byte_perm(e0.y, e0.z, 0x5432), __byte_perm(e0.z, e0.w, 0x5432), __byte_perm(e0.w, n0, 0x5432)));
            sts128(fE + 6208, make_uint4(__byte_perm(e1.x, e1.y, 0x5432), __byte_perm(e1.y, e1.z, 0x5432), __byte_perm(e1.z, e1.w, 0x5432), __byte_perm(e1.w, n1, 0x5432)));
            if (t128 == 0) { sts32(fE, f0); sts128(fE + 4160 - 16, make_uint4(0, 0, 0, f0 << 16)); }
            w_arrive(BAR(B_FO + sf));
            TS1(W0(75 + sf));
          }
        }
      }
    }
    if (t128 < 80) sts64(sb + SM_SILU + t128 * 8, pack2(silu(blo(cv0)), silu(bhi(cv0))), pack2(silu(blo(cv1)), silu(bhi(cv1))));
    fence_async_s();
    bar_sync(1, 128);
    if (bid < 100) {
      float d[16];
      zero_acc<16>(d);
#pragma unroll 1
      for (int s = 0; s < 5; s++) {
        const uint64_t da = mkdesc(sb + s * 16384 + (crank ^ 1) * 8192, 0, 1024, 1), db = mkdesc(sb + SM_SILU + s * 128, 16, 128, 0);
        mbar_wait(BAR(B_WM + s), 0);
        WG_FENCE();
#pragma unroll
        for (int i = 0; i < 4; i++) WSS<8, 1, 0>::mma(d + i * 4, da + i * 128, db + i * 2);
        WG_COMMIT();
      }
      TS1(W0(50));
      WG_WAIT(0);
      float* dst = G->modp + crank * 3200 + (bid >> 1) * 64 + w * 16 + r;
      if (q == 0) { st_relaxed(dst, tagw(__float_as_uint((d[0] + d[4]) + (d[8] + d[12])), par)); st_relaxed(dst + 8, tagw(__float_as_uint((d[2] + d[6]) + (d[10] + d[14])), par)); }
    }
    if (w == 0) w_count(G, C_M + crank);
    w_arrive(BAR(B_WMF));
    TS1(W0(51));
  }
  {
    const int a = w & 1, c = w >> 1;
    const uint32_t qa = rr * 128 + ((4 * c ^ rr) << 4) + mi * 2048 + a * 1024, aa = a * 4096 + (32 * c + r) * 64 + ((q ^ (r >> 1)) << 4);
    uint32_t rs[4], ms[4];
    undef<4>(rs); undef<4>(ms);
#pragma unroll 1
    for (int ph = wg & 1; ph < (STOP_AFTER >= 2 ? 2 : 1); ph++) {
      if (ph) {
        const uint32_t la = sb + SM_LN1 + (a * 16 + (q >> 1) * 8 + r) * 64 + (q & 1) * 8;
        mbar_wait(BAR(B_LN), 0);
        const uint2 u0 = lds64(la), u1 = lds64(la + 16), u2 = lds64(la + 32), u3 = lds64(la + 48);
        const float mu = ((__uint_as_float(u0.x) + __uint_as_float(u1.x)) + (__uint_as_float(u2.x) + __uint_as_float(u3.x))) * (1.f / 640.f);
        const float rq = rsqrtf(fmaxf(((__uint_as_float(u0.y) + __uint_as_float(u1.y)) + (__uint_as_float(u2.y) + __uint_as_float(u3.y))) * (1.f / 640.f) - mu * mu, 0.f) + 1e-5f);
        const uint32_t pk = pack2(rq, -mu * rq);
#pragma unroll
        for (int j = 0; j < 4; j++) {
          const uint32_t e = __shfl_sync(0xffffffffu, pk, 8 * j + q), o = __shfl_sync(0xffffffffu, pk, 8 * j + 4 + q);
          rs[j] = __byte_perm(e, o, 0x5410); ms[j] = __byte_perm(e, o, 0x7632);
        }
        mbar_wait(BAR(B_MT), 0);
        TS1(wg == 2 ? W0(62) : 127);
      }
      float red[16];
#pragma unroll
      for (int i = 0; i < 16; i++) red[i] = 0.f;
#pragma unroll 1
      for (int s = wg & 1; s < 5; s += 1 + ph) {
        const uint32_t own = sb + s * 16384 + crank * 8192;
        uint32_t x[4][4];
        mbar_wait2(BAR(ph ? B_YH + s : B_Q + s), BAR(B_XF + (s & 1)), 0, ((s >> 1) & ph) ^ 1);
        if (CHAIN && ph && s) bar_sync(1 + wg, 256);
        if (!ph) TS1(W0(55 + s)); else if (s == 4) TS2(W0(99));
#pragma unroll
        for (int i = 0; i < 4; i++) ldsm4t(own + (qa ^ (i * 16)), x[i][0], x[i][1], x[i][2], x[i][3]);
        if (ph) {
          const uint4 t0 = lds128(sb + SM_MOD + s * 512 + c * 256 + r * 32), t1 = lds128(sb + SM_MOD + s * 512 + c * 256 + r * 32 + 16);
          const uint32_t cs[4] = {t0.x, t0.z, t1.x, t1.z}, gc[4] = {t0.y, t0.w, t1.y, t1.w};
          uint4 y[4];
#pragma unroll
          for (int i = 0; i < 4; i++) y[i] = lds128(sb + s * 16384 + (crank ^ 1) * 8192 + aa + i * 512);
          stage_end();
          TS2(W0(1 + s));
#pragma unroll 1
          while (any_stale(stale(stale(stale(y[0].x ^ par, y[1].x, par), y[2].x, par), y[3].x, par))) {
            FX(120);
            int l;
            asm volatile("mov.u32 %0, %%laneid;" : "=r"(l));
#pragma unroll
            for (int i = 0; i < 4; i++) y[i] = ld_relaxed4(G->Y + (s * 128 + crank * 64 + c * 32 + i * 8 + (l >> 2)) * 256 + m * 8 + a * 4 + (l & 3));
          }
          if (CHAIN && s < 4) bar_arrive(4 - wg, 256);
          w_arrive_peer(BAR(B_RF + s) + peer);
          bar_sync(wg == 1 ? 5 : 1, 128);
          TS2(W0(10 + s));
          uint32_t rf = 1;
#pragma unroll
          for (int i = 0; i < 4; i++) {
            const uint32_t yv[4] = {y[i].x, y[i].y, y[i].z, y[i].w};
#pragma unroll
            for (int j = 0; j < 4; j++) x[i][j] = bfma2(baffine(bfma2(x[i][j], rs[j], ms[j]), cs[i]), yv[j], x[i][j]);
            y[i] = make_uint4(bmul2(x[i][0], gc[i]), bmul2(x[i][1], gc[i]), bmul2(x[i][2], gc[i]), bmul2(x[i][3], gc[i]));
            sts128(own + aa + i * 512, y[i]);
          }
          if (!BULK_A) rf = mbar_test(BAR(B_RF + s), 0);
          if (s == 2) TS2(W0(97));
          fence_async_s();
          w_arrive(BAR(B_AO + s));
          TS2(W0(20 + s));
          if (!BULK_A) {
            if (any_stale(~rf)) mbar_wait(BAR(B_RF + s), 0);
            st_peer4(own + aa + peer, y, BAR(B_AP + s) + peer);
          }
          if (a == n >> 1) {
            uint32_t xs = sb + SM_X1 + (s & 1) * 4096 - (mi + a) * 1024;
            asm volatile("" : "+r"(xs));
#pragma unroll
            for (int i = 0; i < 4; i++) stsm4t(xs + (qa ^ (i * 16)), x[i][0], x[i][1], x[i][2], x[i][3]);
            fence_async_s();
            w_arrive(BAR(B_XS + s));
          }
        }
        if (s == 2 && ph) TS2(W0(98));
#pragma unroll
        for (int j = 0; j < 4; j++) {
          const uint32_t su = badd2(badd2(x[0][j], x[1][j]), badd2(x[2][j], x[3][j]));
          const uint32_t sq = bfma2(x[3][j], x[3][j], bfma2(x[2][j], x[2][j], bfma2(x[1][j], x[1][j], bmul2(x[0][j], x[0][j]))));
          red[4 * j] += blo(su); red[4 * j + 1] += blo(sq); red[4 * j + 2] += bhi(su); red[4 * j + 3] += bhi(sq);
        }
      }
      int lane;
      asm volatile("mov.u32 %0, %%laneid;" : "=r"(lane));
      const int r = lane >> 2, q = lane & 3;
      bfly<16>(red, lane, 16); bfly<8>(red, lane, 8); bfly<4>(red, lane, 4);
      const uint32_t lb = sb + SM_LNB + w * 256 + lane * 8;
      if (wg == 1) { sts64(lb, __float_as_uint(red[0]), __float_as_uint(red[1])); w_arrive(BAR(B_LNB)); break; }
      if (ph) { mbar_wait(BAR(B_LNB), 0); const uint2 u = lds64(lb); red[0] += __uint_as_float(u.x); red[1] += __uint_as_float(u.y); }
      const uint32_t la = sb + (ph ? SM_LN2 : SM_LN1) + (a * 16 + (q >> 1) * 8 + r) * 64 + (q & 1) * 8;
#pragma unroll
      for (int i = 0; i < 2; i++)
        asm volatile("st.async.weak.shared::cluster.mbarrier::complete_tx::bytes.v2.f32 [%0], {%1, %2}, [%3];" ::"r"(la + (crank * 2 + c) * 16 + i * peer), "f"(red[0]), "f"(red[1]), "r"(BAR(B_LN + ph) + i * peer) : "memory");
      if (ph) TS2(W0(30)); else TS1(W0(60));
    }
  }
  if (wg == 2) {
    if (STOP_AFTER >= 3) {
#pragma unroll 1
      for (int i = 0; i < 5; i++) {
        const int st = i;
        const uint32_t ta = sb + placeB(st) + t128 * 32;
        mbar_wait(BAR(B_FULL2 + st), 0);
        unsigned bad = 0;
#pragma unroll
        for (int k = 0; k < 7; k++) bad = stale(bad, lds32(ta + k * 4096 + r * 4), par);
        if (any_stale(bad)) {
          FX(121);
#pragma unroll 1
          for (int k = 0; k < 7; k++) refetch(ta + k * 4096, G->z2n + (n * 32 + ((i + ROT * (m >> 3)) & 15)) * IMG + k * 256 + t128 * 2, r * 4, par);
        }
        w_arrive(BAR(B_VAL + st));
      }
    }
    if (STOP_AFTER >= 4) {
      mbar_wait(BAR(B_PFREE), 0);
#pragma unroll 1
      for (int e = 0; e < 2; e++) {
        const uint32_t o = sb + e * 14336 + t128 * 16;
        uint4 x[7];
        mbar_wait(BAR(B_PST + e), 0);
#pragma unroll
        for (int k = 0; k < 7; k++) x[k] = lds128(o + SM_PO + k * 2048);
#pragma unroll
        for (int k = 0; k < 7; k++) st_peer(o + peer + k * 2048, x[k], BAR(B_PP + e) + peer);
      }
    }
    goto done;
  }
  asm volatile("setmaxnreg.inc.sync.aligned.u32 192;");
gemm:
  {
    if (STOP_AFTER >= 2) {
      const uint32_t za = sb + SM_PO + (mi >> 1) * 1024 + (16 * w + (mi & 1) * 8 + rr) * 16;
      const bool shifted = !wg ^ (n == 1);
      float k10, k11, sg0 = 0.f, sg1 = 0.f;
      uint32_t zb[2][28], cp = 0;
      const uint2* sp = G->st3 + (m * 4 + q) * 64 + w * 8 + r;
      uint2 s3 = make_uint2(0, 0);
      auto publish = [&](int h, int j0, int j1) {
        if (j0 == 0) {
#pragma unroll 1
          while (any_stale(s3.x ^ par)) { FX(119); s3 = ld_relaxed2(sp + h * 32); }
          TS2(W0(68 + h));
          const float sg = h ? sg1 : sg0, mu = quad_sum(__uint_as_float(s3.x)) * (1.f / 864.f);
          const float c = rsqrtf(fmaf(4e-5f * sg, sg, fmaxf(quad_sum(__uint_as_float(s3.y)) * (1.f / 864.f) - mu * mu, 0.f)));
          cp = pack2(c, -mu * c);
        }
        const uint32_t tg = rr == (m & 1) * 4 + w;
        uint32_t* px = (uint32_t*)(G->z2n + (n * 32 + h * 16 + (m >> 1)) * IMG + (shifted ? 256 : 0) + (m & 1) * 32 + w * 8) + lane;
        uint32_t* py = px - (shifted ? 7168 : 0);
#pragma unroll
        for (int j = j0; j < j1; j++) {
          (j < 24 ? px : py)[j * 256] = h ? baffine(zb[h][j], cp) : bitsel(baffine(zb[h][j], cp), par, tg);
          if (j == FLAG_AT && h == 0 && lane < 8) st_relaxed(G->flagE + (n * 32 + m) * 32 + w * 8 + lane, tag);
        }
        if (j1 == 28) { w_arrive(BAR(B_PUB)); TS2(W0(70 + h)); }
      };
      {
        float z[112];
        undef<112>(z);
        float k20, k21;
        {
          bar_sync(wg ? 7 : 10, 256);
          if (GATEZ) mbar_wait(BAR(B_AO + GATEZ), 0);
#pragma unroll 1
          for (int t = 0; t < 10; t += 2) {
            const int g = wg * 10 + t;
            const uint32_t sx = opaque(sb);
            const uint64_t db = mkdesc(sx + SM_R + (g & 2) * 32768, 8192, 1024, 1), da = mkdesc(sx + t * 8192, 4096, 512, 2);
            const uint32_t fb = BAR(B_FULL1 + (g & 2)), e0 = BAR(t ? B_EMPTY1 + 3 - (g & 2) : B_NIL), x0 = BAR(g == 14 ? B_EMPTY2 : g == 18 ? B_EMPTY2 + 2 : B_NIL), x1 = BAR(g >= 16 ? B_EMPTY2 - 15 + g : B_NIL);
#pragma unroll
            for (int j = 0; j < 2; j++) {
              const uint64_t dx = da + (j ^ crank) * 512;
              mbar_wait2(fb + j * 8, BAR(j ? B_AP : B_AO) + t * 4, (g >> 2) & 1, 0);
              TS2(W0(40 + g + j));
              WG_FENCE();
#pragma unroll
              for (int i = 0; i < 4; i++) WSS<32, 1, 1>::mma(z + 96, dx + i * 64, db + j * 2048 + (shifted ? 4 : 1536) + i * 128, i || j || t);
#pragma unroll
              for (int i = 0; i < 4; i++) WSS<192, 1, 1>::mma(z, dx + i * 64, db + j * 2048 + (shifted ? 512 : 0) + i * 128, i || j || t);
              WG_COMMIT();
              WG_WAIT(1);
              if (lane == 0) { mbar_arrive(j ? fb + (B_EMPTY1 - B_FULL1) * 8 : e0); mbar_arrive(j ? x1 : x0); }
            }
          }
          if (!wg && GATE < 0) bar_arrive(7, 256);
          mbar_wait(BAR(B_LN + 1), 0);
          TS2(W0(60 + wg));
          const float4 y = lds128f(sb + SM_LN2 + t128 * 16);
          const float m0 = quad_sum(y.x) * (1.f / 640.f), m1 = quad_sum(y.z) * (1.f / 640.f);
          const float v0 = fmaxf(quad_sum(y.y) * (1.f / 640.f) - m0 * m0, 0.f) + 1e-5f, v1 = fmaxf(quad_sum(y.w) * (1.f / 640.f) - m1 * m1, 0.f) + 1e-5f;
          const float h0 = rsqrtf(v0), h1 = rsqrtf(v1);
          sg0 = v0 * h0; sg1 = v1 * h1; k10 = h0 * 0.7978845608028f; k11 = h1 * 0.7978845608028f; k20 = h0 * h0 * h0 * 0.0356774081363f; k21 = h1 * h1 * h1 * 0.0356774081363f;
          const uint32_t ext[4] = {ext_frag(m0, sg0, q), ext_frag(m1, sg1, q), 0u, 0u};
          const uint64_t dv = mkdesc(sb + SM_VT, 0, 128, 0);
          mbar_wait(BAR(B_VT), wg);
          WG_FENCE();
          WRS<32>::mma(z + 96, ext, dv + (shifted ? 0 : 192)); WRS<192>::mma(z, ext, dv + (shifted ? 32 : 0));
          WG_COMMIT();
          if (!wg && GATE == 0) bar_arrive(7, 256);
          WG_WAIT(1);
          if (lane == 0) mbar_arrive(BAR(wg ? B_EMPTY2 + 4 : B_EMPTY1 + 1));
          WG_WAIT(0);
          if (wg) bar_sync(5, 128); else if (lane == 0) mbar_arrive(BAR(B_VTF));
          TS2(W0(62 + wg));
        }
        float s0, q0, s1, q1, s2, q2;
        auto gelu = [&](int h, int j0, int j1) {
#pragma unroll
          for (int j = j0; j < j1; j++) {
            const float a = gelu2(z[4 * j + 2 * h], h ? k11 : k10, h ? k21 : k20), b = gelu2(z[4 * j + 2 * h + 1], h ? k11 : k10, h ? k21 : k20);
            zb[h][j] = pack2(a, b);
            if (j == 0) { s0 = a; s1 = b; q0 = a * a; q1 = b * b; }
            else { s0 += a; s1 += b; q0 = fmaf(a, a, q0); q1 = fmaf(b, b, q1); }
            if (j == 23) { s2 = s0 + s1; q2 = q0 + q1; }
          }
          if (j1 == 28) {
            s0 = quad_sum(n == 3 ? s2 : s0 + s1); q0 = quad_sum(n == 3 ? q2 : q0 + q1);
            if (q == n && !wg) st_relaxed2((uint2*)sp + h * 32, tagw(__float_as_uint(s0), par), __float_as_uint(q0));
            TS2(W0(64 + 2 * wg + h));
          }
          stage_end();
        };
        if (HOLD_B && wg && STOP_AFTER >= 3) { mbar_wait(BAR(B_PUB), 0); mbar_wait(BAR(B_PUB), 1); }
        if (GATE > 0) { gelu(0, 0, GATE); if (!wg) bar_arrive(7, 256); }
        gelu(0, GATE > 0 ? GATE : 0, 28);
        gelu(1, 0, LOAD_AT);
        if (!wg) s3 = ld_relaxed2(sp);
        gelu(1, LOAD_AT, PUB_AT);
        if (!wg) publish(0, 0, 28);
        if (PUB_AT < 28) gelu(1, PUB_AT, 28);
        if (STOP_AFTER < 3) { if (!wg) { s3 = ld_relaxed2(sp + 32); publish(1, 0, 28); } }
        else if (wg) {
          uint32_t zx = za + (shifted ? 4096 : 0), zy = za - (shifted ? 24576 : 0);
          asm volatile("" : "+r"(zx), "+r"(zy));
#pragma unroll
          for (int j = 0; j < 28; j += 2) stsm4((j < 24 ? zx : zy) + j * 1024, zb[0][j], zb[1][j], zb[0][j + 1], zb[1][j + 1]);
          w_arrive(BAR(B_Z1S));
        }
        TS2(W0(72 + wg));
      }
      if (STOP_AFTER >= 3) {
        float g[112];
        uint32_t z1[56];
        undef<112>(g);
        const int R0 = (m >> 1) * 128 + (m & 1) * 32 + w * 8 + r;
        const uint32_t bs0 = ldg16(p.bsp + R0), bs1 = ldg16(p.bsp + R0 + 64);
        if (!wg) {
#pragma unroll 1
          for (int rnd = 0;; rnd++) {
            const uint32_t sx = opaque(sb);
            const uint64_t dA2 = mkdesc(sx, 16, 1024, 1), dB2 = mkdesc(sx, 128, 1024, 0);
            const uint32_t fb = BAR(rnd ? B_FULL2 : B_VAL), e0 = BAR(rnd ? B_EMPTY2 + 4 : B_NIL);
#pragma unroll
            for (int st = 0; st < 5; st++) {
              const uint64_t da = dA2 + (placeA(st) >> 4), db = dB2 + (placeB(st) >> 4);
              mbar_wait(fb + st * 8, rnd & 1);
              if (st == 0 || rnd == 0) TS3(W0(st ? 10 + st : 1 + rnd));
              WG_FENCE();
#pragma unroll
              for (int j = 0; j < 4; j++) WSS<96, 0, 1>::mma(g + 64, da + j * 2, db + j * 16 + 1024, st || j || rnd);
#pragma unroll
              for (int j = 0; j < 4; j++) WSS<128, 0, 1>::mma(g, da + j * 2, db + j * 16, st || j || rnd);
              WG_COMMIT();
              WG_WAIT(1);
              if (lane == 0) mbar_arrive(st ? BAR(B_EMPTY2 + st - 1) : e0);
              if (rnd == 0) { if (st) publish(1, 7 * st - 7, 7 * st); else s3 = ld_relaxed2(sp + 32); }
              if (st == 1 && rnd == 6) goto g2_done;
            }
          }
        g2_done:
          w_arrive_peer(BAR(B_PFREE) + peer);
          mbar_wait(BAR(B_Z1S), 0);
        }
        if (!wg || (WARM & 4)) {
          const float c0 = k10 * (0.5f / 0.7978845608028f), c1 = k11 * (0.5f / 0.7978845608028f), e0 = blo(bs0) * c0, e1 = blo(bs1) * c1;
          const float keep = n == 3 ? 0.f : 1.f;
          const uint32_t pa = wg ? sb + SM_DUMMY : za, ps = wg ? 0 : 1024;
          uint32_t* zb = z1;
#pragma unroll
          for (int j = 0; j < 28; j += 2) ldsm4(za + j * 1024, zb[2 * j], zb[2 * j + 1], zb[2 * j + 2], zb[2 * j + 3]);
          WG_WAIT(0);
          if (lane == 0) mbar_arrive(BAR(wg ? B_NIL : B_EMPTY2 + 1));
          TS3(wg ? 127 : W0(20));
#pragma unroll
          for (int j = 0; j < 28; j += 2) {
#pragma unroll
            for (int i = 2 * j; i < 2 * j + 4; i++) {
              const float c = ((i & 1) ? c1 : c0) * (j < 4 ? keep : 1.f), e = ((i & 1) ? e1 : e0) * (j < 4 ? keep : 1.f);
              zb[i] = bmul2(zb[i], pack2(fmaf(g[2 * i], c, e), fmaf(g[2 * i + 1], c, e)));
            }
            stsm4(pa + j * ps, zb[2 * j], zb[2 * j + 1], zb[2 * j + 2], zb[2 * j + 3]);
            if (j == 12 || j == 26) { fence_async_s(); w_arrive(BAR(wg ? B_NIL : B_PST + (j >> 4))); TS3(wg ? 127 : W0(21 + (j >> 4))); }
          }
        }
      }
      if (STOP_AFTER >= 4) {
        float o[64];
        undef<64>(o);
#pragma unroll 1
        for (int it = (WARM & 4) ? wg ^ 1 : 1; it < 2 + wg; it++) {
          if (it) {
            mbar_wait(BAR(B_PST), 0);
#pragma unroll 1
            for (int t = 0; t < 2; t++) {
              const int k = it == 2 ? 8 : 2 - 2 * wg + 4 * t;
              const uint32_t sx = opaque(sb);
              const uint64_t da = mkdesc(sx + (t ? 0 : SM_PO), 1024, 128, 0);
              const uint32_t pb = BAR(t ? B_PP : B_PST);
              if (k && (it == 1 || !t)) bar_sync(12 + wg, 256);
              if (it == 1) {
#pragma unroll
                for (int j = 0; j < 2; j++) {
                  const int st = 1 + ((k + j + 1) & 3);
                  const uint64_t db = mkdesc(sx + placeB(st), 14336, 1024, 1);
                  mbar_wait2(BAR(B_FULL2 + st), pb + j * 8, ((k + j + 1) >> 2) & 1, 0);
                  TS3(W0(30 + k + j));
                  WG_FENCE();
#pragma unroll
                  for (int i = 0; i < 7; i++) WSS<128, 0, 1>::mma(o, da + j * 896 + i * 128, db + i * 128, i || j || t);
                  WG_COMMIT();
                }
                bar_arrive(13 - wg, 256);
                WG_WAIT(1);
                if (lane == 0) mbar_arrive(BAR(B_EMPTY2 + 1 + ((k + 1) & 3)));
                WG_WAIT(0);
                if (lane == 0) mbar_arrive(BAR(B_EMPTY2 + 1 + ((k + 2) & 3)));
              } else {
                const uint64_t db = mkdesc(sx + placeB(2 + t), 0, 1024, 1);
                mbar_wait(BAR(B_FULL2 + 2 + t), 0);
                TS3(W0(38 + t));
                WG_FENCE();
#pragma unroll
                for (int i = 0; i < 14; i++) WSS<64, 0, 1>::mma(o, da + i * 128, db + i * 128, i || t);
                WG_COMMIT();
              }
            }
            mbar_wait(BAR(B_GB), 0);
          }
          const int box = it == 2 ? 4 : 2 - 2 * wg;
#pragma unroll
          for (int b = 0; b < 2; b++) {
            const uint32_t ob = sb + placeA(box + b) + w * 2048, oa = it ? ob + (lane & 15) * 128 + (((mi >> 1) ^ rr) << 4) : sb + SM_DUMMY;
            float4 gb[4];
#pragma unroll
            for (int i = 0; i < 4; i++) gb[i] = lds128f(sb + SM_GB + (box + b) * 256 + i * 64 + q * 16);
            WG_WAIT(0);
            if (b == 0) TS3(W0(it ? 39 + it + 2 * !wg : 127));
#pragma unroll
            for (int i = 0; i < 4; i++) {
              const float* a = o + b * 32 + i * 8;
              stsm4(oa ^ (it ? i * 32 : 0), pack2(a[0] * gb[i].x, a[1] * gb[i].y), pack2(a[2] * gb[i].x, a[3] * gb[i].y), pack2(a[4] * gb[i].z, a[5] * gb[i].w), pack2(a[6] * gb[i].z, a[7] * gb[i].w));
            }
            fence_async_s();
            __syncwarp();
            if (it) tma_rows_add(&tm.out, (box + b) * 128 + crank * 64, m & ~1, (m & 1) * 4 + w, ob);
            TS3(W0(it ? 50 + box + b : 127));
            if (it == 2) break;
          }
        }
        bulk_commit();
        bulk_wait_read0();
        TS3(W0(56 + wg));
      }
    }
  }
done:
  w_arrive(BAR(B_DONE + wg));
}

typedef CUresult (*EncodeFn)(CUtensorMap*, CUtensorMapDataType, cuuint32_t, void*, const cuuint64_t*, const cuuint64_t*, const cuuint32_t*, const cuuint32_t*,
                             CUtensorMapInterleave, CUtensorMapSwizzle, CUtensorMapL2promotion, CUtensorMapFloatOOBfill);
struct Dim { uint64_t size, stride; uint32_t box; };

CUtensorMap make_map(EncodeFn enc, const void* ptr, uint64_t cols, Dim a, Dim b = {0, 0, 0}, Dim c = {0, 0, 0}, Dim d = {0, 0, 0}, uint32_t width = 64) {
  CUtensorMap m;
  cuuint64_t gd[5] = {cols, a.size, b.size, c.size, d.size}, gs[4] = {a.stride, b.stride, c.stride, d.stride};
  cuuint32_t bd[5] = {width, a.box, b.box, c.box, d.box}, es[5] = {1, 1, 1, 1, 1};
  enc(&m, CU_TENSOR_MAP_DATA_TYPE_BFLOAT16, d.size ? 5 : c.size ? 4 : b.size ? 3 : 2, const_cast<void*>(ptr), gd, gs, bd, es, CU_TENSOR_MAP_INTERLEAVE_NONE,
      width == 64 ? CU_TENSOR_MAP_SWIZZLE_128B : width == 32 ? CU_TENSOR_MAP_SWIZZLE_64B : CU_TENSOR_MAP_SWIZZLE_NONE, CU_TENSOR_MAP_L2_PROMOTION_L2_128B, CU_TENSOR_MAP_FLOAT_OOB_FILL_NONE);
  return m;
}

}

extern "C" void kernel_launch(void* const* d_in, const int* in_sizes, int n_in, void* d_out, int out_size) {
  (void)in_sizes; (void)n_in; (void)out_size;
  void* fn = nullptr;
  cudaDriverEntryPointQueryResult qr;
  cudaGetDriverEntryPoint("cuTensorMapEncodeTiled", &fn, cudaEnableDefault, &qr);
  EncodeFn enc = (EncodeFn)fn;
  Params p;
  p.k = (const __nv_bfloat16*)d_in[1]; p.v = (const __nv_bfloat16*)d_in[2];
  p.shiftk = (const __nv_bfloat16*)d_in[3]; p.ssmk = (const __nv_bfloat16*)d_in[4]; p.ssmD = (const __nv_bfloat16*)d_in[5];
  p.bsp = (const __nv_bfloat16*)d_in[9]; p.c = (const __nv_bfloat16*)d_in[11]; p.wout = (const __nv_bfloat16*)d_in[10];
  p.wsp = (const __nv_bfloat16*)d_in[8];
  void* scr = nullptr;
  cudaGetSymbolAddress(&scr, g_scr);
  p.g = (Scratch*)scr;
  int dev = 0, nsm = 0;
  cudaGetDevice(&dev);
  cudaDeviceGetAttribute(&nsm, cudaDevAttrMultiProcessorCount, dev);
  p.by_sm = nsm == 132;
  for (int t = 0; t < 64; t++) {
    const int grp = t < 32 ? t & 7 : t < 60 ? (t - 32) % 7 + 1 : 0, i = t < 32 ? t >> 3 : t < 60 ? 4 + (t - 32) / 7 : t - 56;
    p.tile[t] = ((grp >> 1) * 8 + i) * 2 + (grp & 1);
  }
  const Dim one = {1, 16, 1};
  Maps tm;
  tm.k = make_map(enc, d_in[1], 640, {8, 1280, 10}, {256, 10240, 5}, one, one);
  tm.v = make_map(enc, d_in[2], 640, {8, 1280, 10}, {256, 10240, 4}, one, one);
  tm.f = make_map(enc, d_in[4], 256, {8, 512, 8}, {640, 4096, 1}, one, one, 256);
  tm.wm = make_map(enc, d_in[12], 3840, {640, 7680, 64}, one, one, one);
  tm.q = make_map(enc, d_in[0], 640, {2, 1280, 2}, {32, 81920, 2}, {8, 10240, 4}, {4, 2560, 4});
  tm.y = make_map(enc, p.g->Y, 32, {640, 4096, 64}, {64, 64, 2}, {0, 0, 0}, {0, 0, 0}, 32);
  tm.w2 = make_map(enc, d_in[7], 1728, {640, 3456, 64}, {2, 128, 2});
  tm.wsp = make_map(enc, d_in[8], 2048, {8, 4096, 8}, {32, 262144, 2}, {8, 32768, 4});
  tm.x1 = make_map(enc, d_out, 640, {2, 1280, 2}, {32, 81920, 2}, {8, 10240, 2}, {4, 2560, 4});
  tm.out = make_map(enc, d_out, 640, {8, 1280, 8}, {32, 81920, 2}, {8, 10240, 1});
  tm.wo = make_map(enc, d_in[10], 640, {864, 1280, 112});
  cudaFuncSetAttribute(fused_kernel, cudaFuncAttributeMaxDynamicSharedMemorySize, SM_TOTAL);
  cudaLaunchConfig_t cfg = {};
  cfg.gridDim = dim3(132); cfg.blockDim = dim3(512); cfg.dynamicSmemBytes = SM_TOTAL; cfg.stream = cudaStreamPerThread;
  cudaLaunchAttribute at[1];
  at[0].id = cudaLaunchAttributeCooperative; at[0].val.cooperative = 1;
  cfg.attrs = at; cfg.numAttrs = 1;
  cudaLaunchKernelEx(&cfg, fused_kernel, p, tm);
}
```

```cpp
#include <cuda_runtime.h>
#include <cuda.h>
#include <cuda_bf16.h>
#include <stdint.h>
#include <string.h>
#include <stddef.h>

#define SEQ0 0x1202211101201000ull
#define SEQ1 0x3130231404221303ull
#define SEQ2 0x4342414024343332ull
#define SEQ3 0x44ull
#define WPOS 14
#define T_2 1050
#define T_AB 1800
#define PACE_D 370
#define PACE_F 355
#define PACE_Q 355
#define PACE_W 555
#define T_WIN 13000
#define T_SPARE 11000
#define LOAD_AT 8
#define PUB_AT 16
#define WAIT1 600
#define GATE -1
#define HINT_A 2
#define CHAIN 1
#define PSTEP 4
#define POLL0 1200
#define DELAY0 1600
#define POLL1 600
#define NAPA 700
#define NAPS 1
#define NAPM 500
#define HINT_M 1
#define H2 0
#define ROT 0
#define PONE 1
#define PGATE 3
#define STOP_AFTER 99

namespace {

template<int N> struct WRS;
template<int N, int TA, int TB> struct WSS;
template<> struct WRS<16> { static __device__ __forceinline__ void mma(float* d, const uint32_t* a, uint64_t db) {
  asm volatile("wgmma.mma_async.sync.aligned.m64n16k16.f32.bf16.bf16 {%0,%1,%2,%3,%4,%5,%6,%7}, {%8,%9,%10,%11}, %12, 1, 1, 1, 0;"
    : "+f"(d[0]),"+f"(d[1]),"+f"(d[2]),"+f"(d[3]),"+f"(d[4]),"+f"(d[5]),"+f"(d[6]),"+f"(d[7])
    : "r"(a[0]), "r"(a[1]), "r"(a[2]), "r"(a[3]), "l"(db)); } };
template<> struct WRS<32> { static __device__ __forceinline__ void mma(float* d, const uint32_t* a, uint64_t db) {
  asm volatile("wgmma.mma_async.sync.aligned.m64n32k16.f32.bf16.bf16 {%0,%1,%2,%3,%4,%5,%6,%7,%8,%9,%10,%11,%12,%13,%14,%15}, {%16,%17,%18,%19}, %20, 1, 1, 1, 0;"
    : "+f"(d[0]),"+f"(d[1]),"+f"(d[2]),"+f"(d[3]),"+f"(d[4]),"+f"(d[5]),"+f"(d[6]),"+f"(d[7]),"+f"(d[8]),"+f"(d[9]),"+f"(d[10]),"+f"(d[11]),"+f"(d[12]),"+f"(d[13]),"+f"(d[14]),"+f"(d[15])
    : "r"(a[0]), "r"(a[1]), "r"(a[2]), "r"(a[3]), "l"(db)); } };
template<> struct WRS<48> { static __device__ __forceinline__ void mma(float* d, const uint32_t* a, uint64_t db) {
  asm volatile("wgmma.mma_async.sync.aligned.m64n48k16.f32.bf16.bf16 {%0,%1,%2,%3,%4,%5,%6,%7,%8,%9,%10,%11,%12,%13,%14,%15,%16,%17,%18,%19,%20,%21,%22,%23}, {%24,%25,%26,%27}, %28, 1, 1, 1, 0;"
    : "+f"(d[0]),"+f"(d[1]),"+f"(d[2]),"+f"(d[3]),"+f"(d[4]),"+f"(d[5]),"+f"(d[6]),"+f"(d[7]),"+f"(d[8]),"+f"(d[9]),"+f"(d[10]),"+f"(d[11]),"+f"(d[12]),"+f"(d[13]),"+f"(d[14]),"+f"(d[15]),"+f"(d[16]),"+f"(d[17]),"+f"(d[18]),"+f"(d[19]),"+f"(d[20]),"+f"(d[21]),"+f"(d[22]),"+f"(d[23])
    : "r"(a[0]), "r"(a[1]), "r"(a[2]), "r"(a[3]), "l"(db)); } };
template<> struct WRS<64> { static __device__ __forceinline__ void mma(float* d, const uint32_t* a, uint64_t db) {
  asm volatile("wgmma.mma_async.sync.aligned.m64n64k16.f32.bf16.bf16 {%0,%1,%2,%3,%4,%5,%6,%7,%8,%9,%10,%11,%12,%13,%14,%15,%16,%17,%18,%19,%20,%21,%22,%23,%24,%25,%26,%27,%28,%29,%30,%31}, {%32,%33,%34,%35}, %36, 1, 1, 1, 0;"
    : "+f"(d[0]),"+f"(d[1]),"+f"(d[2]),"+f"(d[3]),"+f"(d[4]),"+f"(d[5]),"+f"(d[6]),"+f"(d[7]),"+f"(d[8]),"+f"(d[9]),"+f"(d[10]),"+f"(d[11]),"+f"(d[12]),"+f"(d[13]),"+f"(d[14]),"+f"(d[15]),"+f"(d[16]),"+f"(d[17]),"+f"(d[18]),"+f"(d[19]),"+f"(d[20]),"+f"(d[21]),"+f"(d[22]),"+f"(d[23]),"+f"(d[24]),"+f"(d[25]),"+f"(d[26]),"+f"(d[27]),"+f"(d[28]),"+f"(d[29]),"+f"(d[30]),"+f"(d[31])
    : "r"(a[0]), "r"(a[1]), "r"(a[2]), "r"(a[3]), "l"(db)); } };
template<> struct WRS<80> { static __device__ __forceinline__ void mma(float* d, const uint32_t* a, uint64_t db) {
  asm volatile("wgmma.mma_async.sync.aligned.m64n80k16.f32.bf16.bf16 {%0,%1,%2,%3,%4,%5,%6,%7,%8,%9,%10,%11,%12,%13,%14,%15,%16,%17,%18,%19,%20,%21,%22,%23,%24,%25,%26,%27,%28,%29,%30,%31,%32,%33,%34,%35,%36,%37,%38,%39}, {%40,%41,%42,%43}, %44, 1, 1, 1, 0;"
    : "+f"(d[0]),"+f"(d[1]),"+f"(d[2]),"+f"(d[3]),"+f"(d[4]),"+f"(d[5]),"+f"(d[6]),"+f"(d[7]),"+f"(d[8]),"+f"(d[9]),"+f"(d[10]),"+f"(d[11]),"+f"(d[12]),"+f"(d[13]),"+f"(d[14]),"+f"(d[15]),"+f"(d[16]),"+f"(d[17]),"+f"(d[18]),"+f"(d[19]),"+f"(d[20]),"+f"(d[21]),"+f"(d[22]),"+f"(d[23]),"+f"(d[24]),"+f"(d[25]),"+f"(d[26]),"+f"(d[27]),"+f"(d[28]),"+f"(d[29]),"+f"(d[30]),"+f"(d[31]),"+f"(d[32]),"+f"(d[33]),"+f"(d[34]),"+f"(d[35]),"+f"(d[36]),"+f"(d[37]),"+f"(d[38]),"+f"(d[39])
    : "r"(a[0]), "r"(a[1]), "r"(a[2]), "r"(a[3]), "l"(db)); } };
template<> struct WRS<96> { static __device__ __forceinline__ void mma(float* d, const uint32_t* a, uint64_t db) {
  asm volatile("wgmma.mma_async.sync.aligned.m64n96k16.f32.bf16.bf16 {%0,%1,%2,%3,%4,%5,%6,%7,%8,%9,%10,%11,%12,%13,%14,%15,%16,%17,%18,%19,%20,%21,%22,%23,%24,%25,%26,%27,%28,%29,%30,%31,%32,%33,%34,%35,%36,%37,%38,%39,%40,%41,%42,%43,%44,%45,%46,%47}, {%48,%49,%50,%51}, %52, 1, 1, 1, 0;"
    : "+f"(d[0]),"+f"(d[1]),"+f"(d[2]),"+f"(d[3]),"+f"(d[4]),"+f"(d[5]),"+f"(d[6]),"+f"(d[7]),"+f"(d[8]),"+f"(d[9]),"+f"(d[10]),"+f"(d[11]),"+f"(d[12]),"+f"(d[13]),"+f"(d[14]),"+f"(d[15]),"+f"(d[16]),"+f"(d[17]),"+f"(d[18]),"+f"(d[19]),"+f"(d[20]),"+f"(d[21]),"+f"(d[22]),"+f"(d[23]),"+f"(d[24]),"+f"(d[25]),"+f"(d[26]),"+f"(d[27]),"+f"(d[28]),"+f"(d[29]),"+f"(d[30]),"+f"(d[31]),"+f"(d[32]),"+f"(d[33]),"+f"(d[34]),"+f"(d[35]),"+f"(d[36]),"+f"(d[37]),"+f"(d[38]),"+f"(d[39]),"+f"(d[40]),"+f"(d[41]),"+f"(d[42]),"+f"(d[43]),"+f"(d[44]),"+f"(d[45]),"+f"(d[46]),"+f"(d[47])
    : "r"(a[0]), "r"(a[1]), "r"(a[2]), "r"(a[3]), "l"(db)); } };
template<> struct WRS<112> { static __device__ __forceinline__ void mma(float* d, const uint32_t* a, uint64_t db) {
  asm volatile("wgmma.mma_async.sync.aligned.m64n112k16.f32.bf16.bf16 {%0,%1,%2,%3,%4,%5,%6,%7,%8,%9,%10,%11,%12,%13,%14,%15,%16,%17,%18,%19,%20,%21,%22,%23,%24,%25,%26,%27,%28,%29,%30,%31,%32,%33,%34,%35,%36,%37,%38,%39,%40,%41,%42,%43,%44,%45,%46,%47,%48,%49,%50,%51,%52,%53,%54,%55}, {%56,%57,%58,%59}, %60, 1, 1, 1, 0;"
    : "+f"(d[0]),"+f"(d[1]),"+f"(d[2]),"+f"(d[3]),"+f"(d[4]),"+f"(d[5]),"+f"(d[6]),"+f"(d[7]),"+f"(d[8]),"+f"(d[9]),"+f"(d[10]),"+f"(d[11]),"+f"(d[12]),"+f"(d[13]),"+f"(d[14]),"+f"(d[15]),"+f"(d[16]),"+f"(d[17]),"+f"(d[18]),"+f"(d[19]),"+f"(d[20]),"+f"(d[21]),"+f"(d[22]),"+f"(d[23]),"+f"(d[24]),"+f"(d[25]),"+f"(d[26]),"+f"(d[27]),"+f"(d[28]),"+f"(d[29]),"+f"(d[30]),"+f"(d[31]),"+f"(d[32]),"+f"(d[33]),"+f"(d[34]),"+f"(d[35]),"+f"(d[36]),"+f"(d[37]),"+f"(d[38]),"+f"(d[39]),"+f"(d[40]),"+f"(d[41]),"+f"(d[42]),"+f"(d[43]),"+f"(d[44]),"+f"(d[45]),"+f"(d[46]),"+f"(d[47]),"+f"(d[48]),"+f"(d[49]),"+f"(d[50]),"+f"(d[51]),"+f"(d[52]),"+f"(d[53]),"+f"(d[54]),"+f"(d[55])
    : "r"(a[0]), "r"(a[1]), "r"(a[2]), "r"(a[3]), "l"(db)); } };
template<> struct WRS<128> { static __device__ __forceinline__ void mma(float* d, const uint32_t* a, uint64_t db) {
  asm volatile("wgmma.mma_async.sync.aligned.m64n128k16.f32.bf16.bf16 {%0,%1,%2,%3,%4,%5,%6,%7,%8,%9,%10,%11,%12,%13,%14,%15,%16,%17,%18,%19,%20,%21,%22,%23,%24,%25,%26,%27,%28,%29,%30,%31,%32,%33,%34,%35,%36,%37,%38,%39,%40,%41,%42,%43,%44,%45,%46,%47,%48,%49,%50,%51,%52,%53,%54,%55,%56,%57,%58,%59,%60,%61,%62,%63}, {%64,%65,%66,%67}, %68, 1, 1, 1, 0;"
    : "+f"(d[0]),"+f"(d[1]),"+f"(d[2]),"+f"(d[3]),"+f"(d[4]),"+f"(d[5]),"+f"(d[6]),"+f"(d[7]),"+f"(d[8]),"+f"(d[9]),"+f"(d[10]),"+f"(d[11]),"+f"(d[12]),"+f"(d[13]),"+f"(d[14]),"+f"(d[15]),"+f"(d[16]),"+f"(d[17]),"+f"(d[18]),"+f"(d[19]),"+f"(d[20]),"+f"(d[21]),"+f"(d[22]),"+f"(d[23]),"+f"(d[24]),"+f"(d[25]),"+f"(d[26]),"+f"(d[27]),"+f"(d[28]),"+f"(d[29]),"+f"(d[30]),"+f"(d[31]),"+f"(d[32]),"+f"(d[33]),"+f"(d[34]),"+f"(d[35]),"+f"(d[36]),"+f"(d[37]),"+f"(d[38]),"+f"(d[39]),"+f"(d[40]),"+f"(d[41]),"+f"(d[42]),"+f"(d[43]),"+f"(d[44]),"+f"(d[45]),"+f"(d[46]),"+f"(d[47]),"+f"(d[48]),"+f"(d[49]),"+f"(d[50]),"+f"(d[51]),"+f"(d[52]),"+f"(d[53]),"+f"(d[54]),"+f"(d[55]),"+f"(d[56]),"+f"(d[57]),"+f"(d[58]),"+f"(d[59]),"+f"(d[60]),"+f"(d[61]),"+f"(d[62]),"+f"(d[63])
    : "r"(a[0]), "r"(a[1]), "r"(a[2]), "r"(a[3]), "l"(db)); } };
template<> struct WRS<192> { static __device__ __forceinline__ void mma(float* d, const uint32_t* a, uint64_t db) {
  asm volatile("wgmma.mma_async.sync.aligned.m64n192k16.f32.bf16.bf16 {%0,%1,%2,%3,%4,%5,%6,%7,%8,%9,%10,%11,%12,%13,%14,%15,%16,%17,%18,%19,%20,%21,%22,%23,%24,%25,%26,%27,%28,%29,%30,%31,%32,%33,%34,%35,%36,%37,%38,%39,%40,%41,%42,%43,%44,%45,%46,%47,%48,%49,%50,%51,%52,%53,%54,%55,%56,%57,%58,%59,%60,%61,%62,%63,%64,%65,%66,%67,%68,%69,%70,%71,%72,%73,%74,%75,%76,%77,%78,%79,%80,%81,%82,%83,%84,%85,%86,%87,%88,%89,%90,%91,%92,%93,%94,%95}, {%96,%97,%98,%99}, %100, 1, 1, 1, 0;"
    : "+f"(d[0]),"+f"(d[1]),"+f"(d[2]),"+f"(d[3]),"+f"(d[4]),"+f"(d[5]),"+f"(d[6]),"+f"(d[7]),"+f"(d[8]),"+f"(d[9]),"+f"(d[10]),"+f"(d[11]),"+f"(d[12]),"+f"(d[13]),"+f"(d[14]),"+f"(d[15]),"+f"(d[16]),"+f"(d[17]),"+f"(d[18]),"+f"(d[19]),"+f"(d[20]),"+f"(d[21]),"+f"(d[22]),"+f"(d[23]),"+f"(d[24]),"+f"(d[25]),"+f"(d[26]),"+f"(d[27]),"+f"(d[28]),"+f"(d[29]),"+f"(d[30]),"+f"(d[31]),"+f"(d[32]),"+f"(d[33]),"+f"(d[34]),"+f"(d[35]),"+f"(d[36]),"+f"(d[37]),"+f"(d[38]),"+f"(d[39]),"+f"(d[40]),"+f"(d[41]),"+f"(d[42]),"+f"(d[43]),"+f"(d[44]),"+f"(d[45]),"+f"(d[46]),"+f"(d[47]),"+f"(d[48]),"+f"(d[49]),"+f"(d[50]),"+f"(d[51]),"+f"(d[52]),"+f"(d[53]),"+f"(d[54]),"+f"(d[55]),"+f"(d[56]),"+f"(d[57]),"+f"(d[58]),"+f"(d[59]),"+f"(d[60]),"+f"(d[61]),"+f"(d[62]),"+f"(d[63]),"+f"(d[64]),"+f"(d[65]),"+f"(d[66]),"+f"(d[67]),"+f"(d[68]),"+f"(d[69]),"+f"(d[70]),"+f"(d[71]),"+f"(d[72]),"+f"(d[73]),"+f"(d[74]),"+f"(d[75]),"+f"(d[76]),"+f"(d[77]),"+f"(d[78]),"+f"(d[79]),"+f"(d[80]),"+f"(d[81]),"+f"(d[82]),"+f"(d[83]),"+f"(d[84]),"+f"(d[85]),"+f"(d[86]),"+f"(d[87]),"+f"(d[88]),"+f"(d[89]),"+f"(d[90]),"+f"(d[91]),"+f"(d[92]),"+f"(d[93]),"+f"(d[94]),"+f"(d[95])
    : "r"(a[0]), "r"(a[1]), "r"(a[2]), "r"(a[3]), "l"(db)); } };
template<> struct WSS<192,1,1> { static __device__ __forceinline__ void mma(float* d, uint64_t da, uint64_t db, int acc = 1) {
  asm volatile("{\n.reg .pred p;\nsetp.ne.b32 p, %98, 0;\nwgmma.mma_async.sync.aligned.m64n192k16.f32.bf16.bf16 {%0,%1,%2,%3,%4,%5,%6,%7,%8,%9,%10,%11,%12,%13,%14,%15,%16,%17,%18,%19,%20,%21,%22,%23,%24,%25,%26,%27,%28,%29,%30,%31,%32,%33,%34,%35,%36,%37,%38,%39,%40,%41,%42,%43,%44,%45,%46,%47,%48,%49,%50,%51,%52,%53,%54,%55,%56,%57,%58,%59,%60,%61,%62,%63,%64,%65,%66,%67,%68,%69,%70,%71,%72,%73,%74,%75,%76,%77,%78,%79,%80,%81,%82,%83,%84,%85,%86,%87,%88,%89,%90,%91,%92,%93,%94,%95}, %96, %97, p, 1, 1, 1, 1;\n}"
    : "+f"(d[0]),"+f"(d[1]),"+f"(d[2]),"+f"(d[3]),"+f"(d[4]),"+f"(d[5]),"+f"(d[6]),"+f"(d[7]),"+f"(d[8]),"+f"(d[9]),"+f"(d[10]),"+f"(d[11]),"+f"(d[12]),"+f"(d[13]),"+f"(d[14]),"+f"(d[15]),"+f"(d[16]),"+f"(d[17]),"+f"(d[18]),"+f"(d[19]),"+f"(d[20]),"+f"(d[21]),"+f"(d[22]),"+f"(d[23]),"+f"(d[24]),"+f"(d[25]),"+f"(d[26]),"+f"(d[27]),"+f"(d[28]),"+f"(d[29]),"+f"(d[30]),"+f"(d[31]),"+f"(d[32]),"+f"(d[33]),"+f"(d[34]),"+f"(d[35]),"+f"(d[36]),"+f"(d[37]),"+f"(d[38]),"+f"(d[39]),"+f"(d[40]),"+f"(d[41]),"+f"(d[42]),"+f"(d[43]),"+f"(d[44]),"+f"(d[45]),"+f"(d[46]),"+f"(d[47]),"+f"(d[48]),"+f"(d[49]),"+f"(d[50]),"+f"(d[51]),"+f"(d[52]),"+f"(d[53]),"+f"(d[54]),"+f"(d[55]),"+f"(d[56]),"+f"(d[57]),"+f"(d[58]),"+f"(d[59]),"+f"(d[60]),"+f"(d[61]),"+f"(d[62]),"+f"(d[63]),"+f"(d[64]),"+f"(d[65]),"+f"(d[66]),"+f"(d[67]),"+f"(d[68]),"+f"(d[69]),"+f"(d[70]),"+f"(d[71]),"+f"(d[72]),"+f"(d[73]),"+f"(d[74]),"+f"(d[75]),"+f"(d[76]),"+f"(d[77]),"+f"(d[78]),"+f"(d[79]),"+f"(d[80]),"+f"(d[81]),"+f"(d[82]),"+f"(d[83]),"+f"(d[84]),"+f"(d[85]),"+f"(d[86]),"+f"(d[87]),"+f"(d[88]),"+f"(d[89]),"+f"(d[90]),"+f"(d[91]),"+f"(d[92]),"+f"(d[93]),"+f"(d[94]),"+f"(d[95])
    : "l"(da), "l"(db), "r"(acc)); } };
template<> struct WSS<32,1,1> { static __device__ __forceinline__ void mma(float* d, uint64_t da, uint64_t db, int acc = 1) {
  asm volatile("{\n.reg .pred p;\nsetp.ne.b32 p, %18, 0;\nwgmma.mma_async.sync.aligned.m64n32k16.f32.bf16.bf16 {%0,%1,%2,%3,%4,%5,%6,%7,%8,%9,%10,%11,%12,%13,%14,%15}, %16, %17, p, 1, 1, 1, 1;\n}"
    : "+f"(d[0]),"+f"(d[1]),"+f"(d[2]),"+f"(d[3]),"+f"(d[4]),"+f"(d[5]),"+f"(d[6]),"+f"(d[7]),"+f"(d[8]),"+f"(d[9]),"+f"(d[10]),"+f"(d[11]),"+f"(d[12]),"+f"(d[13]),"+f"(d[14]),"+f"(d[15])
    : "l"(da), "l"(db), "r"(acc)); } };
template<> struct WSS<128,0,1> { static __device__ __forceinline__ void mma(float* d, uint64_t da, uint64_t db, int acc = 1) {
  asm volatile("{\n.reg .pred p;\nsetp.ne.b32 p, %66, 0;\nwgmma.mma_async.sync.aligned.m64n128k16.f32.bf16.bf16 {%0,%1,%2,%3,%4,%5,%6,%7,%8,%9,%10,%11,%12,%13,%14,%15,%16,%17,%18,%19,%20,%21,%22,%23,%24,%25,%26,%27,%28,%29,%30,%31,%32,%33,%34,%35,%36,%37,%38,%39,%40,%41,%42,%43,%44,%45,%46,%47,%48,%49,%50,%51,%52,%53,%54,%55,%56,%57,%58,%59,%60,%61,%62,%63}, %64, %65, p, 1, 1, 0, 1;\n}"
    : "+f"(d[0]),"+f"(d[1]),"+f"(d[2]),"+f"(d[3]),"+f"(d[4]),"+f"(d[5]),"+f"(d[6]),"+f"(d[7]),"+f"(d[8]),"+f"(d[9]),"+f"(d[10]),"+f"(d[11]),"+f"(d[12]),"+f"(d[13]),"+f"(d[14]),"+f"(d[15]),"+f"(d[16]),"+f"(d[17]),"+f"(d[18]),"+f"(d[19]),"+f"(d[20]),"+f"(d[21]),"+f"(d[22]),"+f"(d[23]),"+f"(d[24]),"+f"(d[25]),"+f"(d[26]),"+f"(d[27]),"+f"(d[28]),"+f"(d[29]),"+f"(d[30]),"+f"(d[31]),"+f"(d[32]),"+f"(d[33]),"+f"(d[34]),"+f"(d[35]),"+f"(d[36]),"+f"(d[37]),"+f"(d[38]),"+f"(d[39]),"+f"(d[40]),"+f"(d[41]),"+f"(d[42]),"+f"(d[43]),"+f"(d[44]),"+f"(d[45]),"+f"(d[46]),"+f"(d[47]),"+f"(d[48]),"+f"(d[49]),"+f"(d[50]),"+f"(d[51]),"+f"(d[52]),"+f"(d[53]),"+f"(d[54]),"+f"(d[55]),"+f"(d[56]),"+f"(d[57]),"+f"(d[58]),"+f"(d[59]),"+f"(d[60]),"+f"(d[61]),"+f"(d[62]),"+f"(d[63])
    : "l"(da), "l"(db), "r"(acc)); } };
template<> struct WSS<96,0,1> { static __device__ __forceinline__ void mma(float* d, uint64_t da, uint64_t db, int acc = 1) {
  asm volatile("{\n.reg .pred p;\nsetp.ne.b32 p, %50, 0;\nwgmma.mma_async.sync.aligned.m64n96k16.f32.bf16.bf16 {%0,%1,%2,%3,%4,%5,%6,%7,%8,%9,%10,%11,%12,%13,%14,%15,%16,%17,%18,%19,%20,%21,%22,%23,%24,%25,%26,%27,%28,%29,%30,%31,%32,%33,%34,%35,%36,%37,%38,%39,%40,%41,%42,%43,%44,%45,%46,%47}, %48, %49, p, 1, 1, 0, 1;\n}"
    : "+f"(d[0]),"+f"(d[1]),"+f"(d[2]),"+f"(d[3]),"+f"(d[4]),"+f"(d[5]),"+f"(d[6]),"+f"(d[7]),"+f"(d[8]),"+f"(d[9]),"+f"(d[10]),"+f"(d[11]),"+f"(d[12]),"+f"(d[13]),"+f"(d[14]),"+f"(d[15]),"+f"(d[16]),"+f"(d[17]),"+f"(d[18]),"+f"(d[19]),"+f"(d[20]),"+f"(d[21]),"+f"(d[22]),"+f"(d[23]),"+f"(d[24]),"+f"(d[25]),"+f"(d[26]),"+f"(d[27]),"+f"(d[28]),"+f"(d[29]),"+f"(d[30]),"+f"(d[31]),"+f"(d[32]),"+f"(d[33]),"+f"(d[34]),"+f"(d[35]),"+f"(d[36]),"+f"(d[37]),"+f"(d[38]),"+f"(d[39]),"+f"(d[40]),"+f"(d[41]),"+f"(d[42]),"+f"(d[43]),"+f"(d[44]),"+f"(d[45]),"+f"(d[46]),"+f"(d[47])
    : "l"(da), "l"(db), "r"(acc)); } };
template<> struct WSS<64,0,1> { static __device__ __forceinline__ void mma(float* d, uint64_t da, uint64_t db, int acc = 1) {
  asm volatile("{\n.reg .pred p;\nsetp.ne.b32 p, %34, 0;\nwgmma.mma_async.sync.aligned.m64n64k16.f32.bf16.bf16 {%0,%1,%2,%3,%4,%5,%6,%7,%8,%9,%10,%11,%12,%13,%14,%15,%16,%17,%18,%19,%20,%21,%22,%23,%24,%25,%26,%27,%28,%29,%30,%31}, %32, %33, p, 1, 1, 0, 1;\n}"
    : "+f"(d[0]),"+f"(d[1]),"+f"(d[2]),"+f"(d[3]),"+f"(d[4]),"+f"(d[5]),"+f"(d[6]),"+f"(d[7]),"+f"(d[8]),"+f"(d[9]),"+f"(d[10]),"+f"(d[11]),"+f"(d[12]),"+f"(d[13]),"+f"(d[14]),"+f"(d[15]),"+f"(d[16]),"+f"(d[17]),"+f"(d[18]),"+f"(d[19]),"+f"(d[20]),"+f"(d[21]),"+f"(d[22]),"+f"(d[23]),"+f"(d[24]),"+f"(d[25]),"+f"(d[26]),"+f"(d[27]),"+f"(d[28]),"+f"(d[29]),"+f"(d[30]),"+f"(d[31])
    : "l"(da), "l"(db), "r"(acc)); } };
template<> struct WSS<8,1,0> { static __device__ __forceinline__ void mma(float* d, uint64_t da, uint64_t db, int acc = 1) {
  asm volatile("{\n.reg .pred p;\nsetp.ne.b32 p, %6, 0;\nwgmma.mma_async.sync.aligned.m64n8k16.f32.bf16.bf16 {%0,%1,%2,%3}, %4, %5, p, 1, 1, 1, 0;\n}"
    : "+f"(d[0]),"+f"(d[1]),"+f"(d[2]),"+f"(d[3])
    : "l"(da), "l"(db), "r"(acc)); } };
__device__ __forceinline__ void wrs128_first(float* d, const uint32_t* a, uint64_t db) {
  asm volatile("wgmma.mma_async.sync.aligned.m64n128k16.f32.bf16.bf16 {%0,%1,%2,%3,%4,%5,%6,%7,%8,%9,%10,%11,%12,%13,%14,%15,%16,%17,%18,%19,%20,%21,%22,%23,%24,%25,%26,%27,%28,%29,%30,%31,%32,%33,%34,%35,%36,%37,%38,%39,%40,%41,%42,%43,%44,%45,%46,%47,%48,%49,%50,%51,%52,%53,%54,%55,%56,%57,%58,%59,%60,%61,%62,%63}, {%64,%65,%66,%67}, %68, 0, 1, 1, 0;"
    : "=f"(d[0]),"=f"(d[1]),"=f"(d[2]),"=f"(d[3]),"=f"(d[4]),"=f"(d[5]),"=f"(d[6]),"=f"(d[7]),"=f"(d[8]),"=f"(d[9]),"=f"(d[10]),"=f"(d[11]),"=f"(d[12]),"=f"(d[13]),"=f"(d[14]),"=f"(d[15]),"=f"(d[16]),"=f"(d[17]),"=f"(d[18]),"=f"(d[19]),"=f"(d[20]),"=f"(d[21]),"=f"(d[22]),"=f"(d[23]),"=f"(d[24]),"=f"(d[25]),"=f"(d[26]),"=f"(d[27]),"=f"(d[28]),"=f"(d[29]),"=f"(d[30]),"=f"(d[31]),"=f"(d[32]),"=f"(d[33]),"=f"(d[34]),"=f"(d[35]),"=f"(d[36]),"=f"(d[37]),"=f"(d[38]),"=f"(d[39]),"=f"(d[40]),"=f"(d[41]),"=f"(d[42]),"=f"(d[43]),"=f"(d[44]),"=f"(d[45]),"=f"(d[46]),"=f"(d[47]),"=f"(d[48]),"=f"(d[49]),"=f"(d[50]),"=f"(d[51]),"=f"(d[52]),"=f"(d[53]),"=f"(d[54]),"=f"(d[55]),"=f"(d[56]),"=f"(d[57]),"=f"(d[58]),"=f"(d[59]),"=f"(d[60]),"=f"(d[61]),"=f"(d[62]),"=f"(d[63])
    : "r"(a[0]), "r"(a[1]), "r"(a[2]), "r"(a[3]), "l"(db)); }
__device__ __forceinline__ void wrs96_first(float* d, const uint32_t* a, uint64_t db) {
  asm volatile("wgmma.mma_async.sync.aligned.m64n96k16.f32.bf16.bf16 {%0,%1,%2,%3,%4,%5,%6,%7,%8,%9,%10,%11,%12,%13,%14,%15,%16,%17,%18,%19,%20,%21,%22,%23,%24,%25,%26,%27,%28,%29,%30,%31,%32,%33,%34,%35,%36,%37,%38,%39,%40,%41,%42,%43,%44,%45,%46,%47}, {%48,%49,%50,%51}, %52, 0, 1, 1, 0;"
    : "=f"(d[0]),"=f"(d[1]),"=f"(d[2]),"=f"(d[3]),"=f"(d[4]),"=f"(d[5]),"=f"(d[6]),"=f"(d[7]),"=f"(d[8]),"=f"(d[9]),"=f"(d[10]),"=f"(d[11]),"=f"(d[12]),"=f"(d[13]),"=f"(d[14]),"=f"(d[15]),"=f"(d[16]),"=f"(d[17]),"=f"(d[18]),"=f"(d[19]),"=f"(d[20]),"=f"(d[21]),"=f"(d[22]),"=f"(d[23]),"=f"(d[24]),"=f"(d[25]),"=f"(d[26]),"=f"(d[27]),"=f"(d[28]),"=f"(d[29]),"=f"(d[30]),"=f"(d[31]),"=f"(d[32]),"=f"(d[33]),"=f"(d[34]),"=f"(d[35]),"=f"(d[36]),"=f"(d[37]),"=f"(d[38]),"=f"(d[39]),"=f"(d[40]),"=f"(d[41]),"=f"(d[42]),"=f"(d[43]),"=f"(d[44]),"=f"(d[45]),"=f"(d[46]),"=f"(d[47])
    : "r"(a[0]), "r"(a[1]), "r"(a[2]), "r"(a[3]), "l"(db)); }

constexpr int IMG = 1792;
struct Scratch {
  unsigned cnt[32 * 32];
  float modp[2 * 3200];
  float gb[640];
  uint4 vt[8 * 224];
  uint2 st3[128 * 64];
  uint4 T[640 * 256];
  uint4 Y[640 * 256];
  uint4 z2n[4 * 32 * IMG];
};
__device__ __align__(1024) Scratch g_scr;
enum { C_A = 0, C_Y = 10, C_M = 20, C_G = 22, C_H = 24  , C_E = 28 };

constexpr uint32_t SM_R = 81920, SM_PO = 184320, SM_S = 212992, SM_X1 = 221184, SM_TAIL = 229376, SM_TOTAL = 232448;
constexpr uint32_t KV_V = 7168;
constexpr uint32_t SM_VT = SM_S, SM_LN1 = SM_S, SM_MOD = SM_S + 3584, SM_LN2 = SM_S + 6144, SM_SILU = SM_LN2;
constexpr uint32_t SM_BAR = SM_TAIL, SM_TPC = SM_BAR + 912, SM_DUMMY = SM_TPC + 48, SM_LNB = SM_DUMMY + 64, SM_PROF = SM_LNB + 1024, SM_ONE = SM_PROF + 512, SM_GB = SM_MOD;
static_assert(SM_ONE + 128 <= SM_TOTAL, "smem");
__device__ __forceinline__ uint32_t offU(int s) { return SM_R + ((0x64302u >> (4 * s)) & 15) * 16384; }
__device__ __forceinline__ uint32_t offF(int s) { return offU(s) + 4208; }
__host__ __device__ constexpr uint32_t placeB(int st) { return ((uint32_t)(0x9874245000ull >> (8 * st)) & 255) * 1024; }
__host__ __device__ constexpr uint32_t placeA(int st) { return ((uint32_t)(0x40906C1CD8ull >> (8 * st)) & 255) * 1024; }
__device__ __forceinline__ int nstart(int n) { return n < 3 ? 224 * n : 640; }
enum {
  B_KV = 0, B_F = 5, B_WM = 10, B_Q = 15, B_U = 20, B_YH = 25  , B_AP = 31, B_LN = 36  , B_PP = 38  ,
  B_XF = 40  , B_VT = 42, B_X1D = 45, B_ACK = 43, B_GB = 44, B_LOK = 47  ,
  B_FULL1 = 50, B_FULL2 = 54,
  B_KVF = 64, B_EMPTY1 = 69, B_EMPTY2 = 73, B_VAL = 78, B_PST = 83  , B_VTF = 85, B_PUB = 86, B_Z1S = 87, B_PFREE = 88, B_NIL = 89,
  B_DONE = 90  , B_AO = 94, B_LNB = 99, B_RF = 100, B_MT = 105, B_WMF = 106, B_FO = 107
};

struct Params {
  const __nv_bfloat16 *k, *v, *ssmk;
  Scratch* g;
  const __nv_bfloat16* shiftk;
  int by_sm;
  const __nv_bfloat16 *c, *ssmD, *bsp, *wout, *wsp;
  uint8_t tile[64];
};

struct Maps { CUtensorMap k, v, f, wm, q, y, w2, x1, wsp, out, wo, wm2; };

__device__ __forceinline__ void mbar_arrive(uint32_t a) { asm volatile("mbarrier.arrive.shared::cta.b64 _, [%0];" ::"r"(a) : "memory"); }
__device__ __forceinline__ void mbar_expect(uint32_t a, int b) { asm volatile("mbarrier.arrive.expect_tx.shared::cta.b64 _, [%0], %1;" ::"r"(a), "r"(b) : "memory"); }
__device__ __forceinline__ void mbar_wait(uint32_t a, int ph) {
  asm volatile("{\n.reg .pred p;\nWL:\nmbarrier.try_wait.parity.shared::cta.b64 p, [%0], %1;\n@!p bra WL;\n}" ::"r"(a), "r"(ph) : "memory");
}
__device__ __forceinline__ void mbar_wait2(uint32_t a, uint32_t b, int pa, int pb) {
  asm volatile("{\n.reg .pred p, q;\nWL:\nmbarrier.try_wait.parity.shared::cta.b64 p, [%0], %2;\nmbarrier.try_wait.parity.shared::cta.b64 q, [%1], %3;\nand.pred p, p, q;\n@!p bra WL;\n}" ::"r"(a), "r"(b), "r"(pa), "r"(pb) : "memory");
}
__device__ __forceinline__ uint32_t mbar_test(uint32_t a, int ph) {
  uint32_t r;
  asm volatile("{\n.reg .pred p;\nmbarrier.test_wait.parity.shared::cta.b64 p, [%1], %2;\nselp.u32 %0, 1, 0, p;\n}" : "=r"(r) : "r"(a), "r"(ph) : "memory");
  return r;
}
__device__ __forceinline__ void mbar_wait_b(uint32_t a, int ph) {
  asm volatile("{\n.reg .pred p;\n.reg .u32 c;\nmov.u32 c, 0;\nWL:\nmbarrier.try_wait.parity.shared::cta.b64 p, [%0], %1;\n@p bra WD;\n"
               "add.u32 c, c, 1;\nsetp.lt.u32 p, c, 0x10000;\n@p bra WL;\ntrap;\nWD:\n}" ::"r"(a), "r"(ph) : "memory");
}
__device__ __forceinline__ uint32_t mapa(uint32_t a, uint32_t rank) { uint32_t r; asm("mapa.shared::cluster.u32 %0, %1, %2;" : "=r"(r) : "r"(a), "r"(rank)); return r; }
__device__ __forceinline__ void bar_sync(int id, int n) { asm volatile("bar.sync %0, %1;" ::"r"(id), "r"(n) : "memory"); }
__device__ __forceinline__ void bar_arrive(int id, int n) { asm volatile("bar.arrive %0, %1;" ::"r"(id), "r"(n) : "memory"); }
__device__ __forceinline__ unsigned ld_acquire(const void* p) { unsigned v; asm volatile("ld.acquire.gpu.global.u32 %0, [%1];" : "=r"(v) : "l"(p) : "memory"); return v; }
__device__ __forceinline__ unsigned ld_relaxed(const void* p) { unsigned v; asm volatile("ld.relaxed.gpu.global.u32 %0, [%1];" : "=r"(v) : "l"(p) : "memory"); return v; }
__device__ __forceinline__ uint4 ld_relaxed4(const void* p) { uint4 v; asm volatile("ld.relaxed.gpu.global.v4.u32 {%0,%1,%2,%3}, [%4];" : "=r"(v.x), "=r"(v.y), "=r"(v.z), "=r"(v.w) : "l"(p) : "memory"); return v; }
__device__ __forceinline__ void st_relaxed4(void* p, uint4 v) { asm volatile("st.relaxed.gpu.global.v4.u32 [%0], {%1,%2,%3,%4};" ::"l"(p), "r"(v.x), "r"(v.y), "r"(v.z), "r"(v.w) : "memory"); }
__device__ __forceinline__ uint2 ld_relaxed2(const void* p) { uint2 v; asm volatile("ld.relaxed.gpu.global.v2.u32 {%0,%1}, [%2];" : "=r"(v.x), "=r"(v.y) : "l"(p) : "memory"); return v; }
__device__ __forceinline__ void st_relaxed2(void* p, uint32_t a, uint32_t b) { asm volatile("st.relaxed.gpu.global.v2.u32 [%0], {%1,%2};" ::"l"(p), "r"(a), "r"(b) : "memory"); }
__device__ __forceinline__ void st_relaxed(void* p, unsigned v) { asm volatile("st.relaxed.gpu.global.u32 [%0], %1;" ::"l"(p), "r"(v) : "memory"); }
__device__ __forceinline__ void fence_gpu() { asm volatile("fence.acq_rel.gpu;" ::: "memory"); }
__device__ __forceinline__ void wait_cnt(const unsigned* c, unsigned target) {
#pragma unroll 1
  while (__any_sync(0xffffffffu, (int)(ld_relaxed(c) - target) < 0)) {}
}
__device__ __forceinline__ void fence_async_g() { asm volatile("fence.proxy.async.global;" ::: "memory"); }
__device__ __forceinline__ void fence_async_s() { asm volatile("fence.proxy.async.shared::cta;" ::: "memory"); }
#define ELECT "{\n.reg .pred e;\nelect.sync _|e, 0xffffffff;\n@e "
__device__ __forceinline__ void w_expect(uint32_t a, int b) { asm volatile(ELECT "mbarrier.arrive.expect_tx.shared::cta.b64 _, [%0], %1;\n}" ::"r"(a), "r"(b) : "memory"); }
__device__ __forceinline__ void bulk_g2s(uint32_t dst, const void* src, int bytes, uint32_t bar) {
  asm volatile(ELECT "cp.async.bulk.shared::cluster.global.mbarrier::complete_tx::bytes [%0], [%1], %2, [%3];\n}" ::"r"(dst), "l"(src), "r"(bytes), "r"(bar) : "memory");
}
__device__ __forceinline__ void bulk_commit() { asm volatile("cp.async.bulk.commit_group;" ::: "memory"); }
__device__ __forceinline__ void bulk_wait_read0() { asm volatile("cp.async.bulk.wait_group.read 0;" ::: "memory"); }
__device__ __forceinline__ void tma2d(uint32_t dst, const CUtensorMap* m, int c0, int c1, uint32_t bar) {
  asm volatile(ELECT "cp.async.bulk.tensor.2d.shared::cluster.global.mbarrier::complete_tx::bytes [%0], [%1, {%3, %4}], [%2];\n}" ::"r"(dst), "l"(m), "r"(bar), "r"(c0), "r"(c1) : "memory");
}
__device__ __forceinline__ void tma3d(uint32_t dst, const CUtensorMap* m, int c0, int c1, int c2, uint32_t bar) {
  asm volatile(ELECT "cp.async.bulk.tensor.3d.shared::cluster.global.mbarrier::complete_tx::bytes [%0], [%1, {%3, %4, %5}], [%2];\n}" ::"r"(dst), "l"(m), "r"(bar), "r"(c0), "r"(c1), "r"(c2) : "memory");
}
__device__ __forceinline__ void tma_rows(uint32_t dst, const CUtensorMap* m, int c0, int c2, int c3, uint32_t bar) {
  asm volatile(ELECT "cp.async.bulk.tensor.4d.shared::cluster.global.mbarrier::complete_tx::bytes [%0], [%1, {%3, %6, %4, %5}], [%2];\n}" ::"r"(dst), "l"(m), "r"(bar), "r"(c0), "r"(c2), "r"(c3), "r"(0) : "memory");
}
__device__ __forceinline__ void tma_rows_add(const CUtensorMap* m, int c0, int c2, int c3, uint32_t src) {
  asm volatile(ELECT "cp.reduce.async.bulk.tensor.4d.global.shared::cta.add.tile.bulk_group [%0, {%2, %5, %3, %4}], [%1];\n}" ::"l"(m), "r"(src), "r"(c0), "r"(c2), "r"(c3), "r"(0) : "memory");
}
__device__ __forceinline__ void tma5d(uint32_t dst, const CUtensorMap* m, int c0, int c1, int c2, int c3, uint32_t bar) {
  asm volatile(ELECT "cp.async.bulk.tensor.5d.shared::cluster.global.mbarrier::complete_tx::bytes [%0], [%1, {%3, %4, %5, %6, %7}], [%2];\n}" ::"r"(dst), "l"(m), "r"(bar), "r"(c0), "r"(c1), "r"(c2), "r"(c3), "r"(0) : "memory");
}
__device__ __forceinline__ void tma5d_store(const CUtensorMap* m, int c0, int c2, int c3, uint32_t src) {
  asm volatile(ELECT "cp.async.bulk.tensor.5d.global.shared::cta.bulk_group [%0, {%2, %5, %3, %4, %5}], [%1];\n}" ::"l"(m), "r"(src), "r"(c0), "r"(c2), "r"(c3), "r"(0) : "memory");
}
__device__ __forceinline__ void bulk_s2peer(uint32_t rdst, uint32_t src, int bytes, uint32_t rbar) {
  asm volatile(ELECT "cp.async.bulk.shared::cluster.shared::cta.mbarrier::complete_tx::bytes [%0], [%1], %2, [%3];\n}" ::"r"(rdst), "r"(src), "r"(bytes), "r"(rbar) : "memory");
}
__device__ __forceinline__ void w_count(const Scratch* G, int idx) { asm volatile(ELECT "red.relaxed.gpu.global.add.u32 [%0], 1;\n}" ::"l"(G->cnt + idx * 32) : "memory"); }
__device__ __forceinline__ void w_count_timed(const Scratch* G, int idx) {
  asm volatile("{\n.reg .pred e;\n.reg .u64 t;\nelect.sync _|e, 0xffffffff;\nmov.u64 t, %%globaltimer;\n@e red.relaxed.gpu.global.max.u64 [%0+8], t;\n@e red.relaxed.gpu.global.add.u32 [%0], 1;\n}" ::"l"(G->cnt + idx * 32) : "memory");
}
__device__ __forceinline__ void w_arrive(uint32_t a) { asm volatile(ELECT "mbarrier.arrive.shared::cta.b64 _, [%0];\n}" ::"r"(a) : "memory"); }
__device__ __forceinline__ void w_arrive_peer(uint32_t ra) { asm volatile(ELECT "mbarrier.arrive.shared::cluster.b64 _, [%0];\n}" ::"r"(ra) : "memory"); }
__device__ __forceinline__ void tmap_prefetch(const CUtensorMap* m) { asm volatile("prefetch.tensormap [%0];" ::"l"(m) : "memory"); }
__device__ __forceinline__ uint64_t mkdesc(uint32_t addr, uint32_t lbo, uint32_t sbo, uint32_t swz) {
  return (uint64_t)((addr & 0x3FFFF) >> 4) | ((uint64_t)(lbo >> 4) << 16) | ((uint64_t)(sbo >> 4) << 32) | ((uint64_t)swz << 62);
}
#define WG_FENCE() asm volatile("wgmma.fence.sync.aligned;" ::: "memory")
#define WG_COMMIT() asm volatile("wgmma.commit_group.sync.aligned;" ::: "memory")
#define WG_WAIT(n) asm volatile("wgmma.wait_group.sync.aligned " #n ";" ::: "memory")
__device__ __forceinline__ uint32_t lds32(uint32_t a) { uint32_t v; asm volatile("ld.shared.u32 %0, [%1];" : "=r"(v) : "r"(a) : "memory"); return v; }
__device__ __forceinline__ uint2 lds64(uint32_t a) { uint2 v; asm volatile("ld.shared.v2.u32 {%0,%1}, [%2];" : "=r"(v.x), "=r"(v.y) : "r"(a) : "memory"); return v; }
__device__ __forceinline__ uint4 lds128(uint32_t a) { uint4 v; asm volatile("ld.shared.v4.u32 {%0,%1,%2,%3}, [%4];" : "=r"(v.x), "=r"(v.y), "=r"(v.z), "=r"(v.w) : "r"(a) : "memory"); return v; }
__device__ __forceinline__ float4 lds128f(uint32_t a) { float4 v; asm volatile("ld.shared.v4.f32 {%0,%1,%2,%3}, [%4];" : "=f"(v.x), "=f"(v.y), "=f"(v.z), "=f"(v.w) : "r"(a) : "memory"); return v; }
__device__ __forceinline__ void sts32(uint32_t a, uint32_t v) { asm volatile("st.shared.u32 [%0], %1;" ::"r"(a), "r"(v) : "memory"); }
__device__ __forceinline__ void sts64(uint32_t a, uint32_t x, uint32_t y) { asm volatile("st.shared.v2.u32 [%0], {%1,%2};" ::"r"(a), "r"(x), "r"(y) : "memory"); }
__device__ __forceinline__ void sts128(uint32_t a, uint4 v) { asm volatile("st.shared.v4.u32 [%0], {%1,%2,%3,%4};" ::"r"(a), "r"(v.x), "r"(v.y), "r"(v.z), "r"(v.w) : "memory"); }
__device__ __forceinline__ void stsm4(uint32_t a, uint32_t r0, uint32_t r1, uint32_t r2, uint32_t r3) {
  asm volatile("stmatrix.sync.aligned.m8n8.x4.shared.b16 [%0], {%1,%2,%3,%4};" ::"r"(a), "r"(r0), "r"(r1), "r"(r2), "r"(r3) : "memory");
}
__device__ __forceinline__ void stsm4t(uint32_t a, uint32_t r0, uint32_t r1, uint32_t r2, uint32_t r3) {
  asm volatile("stmatrix.sync.aligned.m8n8.x4.trans.shared.b16 [%0], {%1,%2,%3,%4};" ::"r"(a), "r"(r0), "r"(r1), "r"(r2), "r"(r3) : "memory");
}
__device__ __forceinline__ void ldsm4(uint32_t a, uint32_t& r0, uint32_t& r1, uint32_t& r2, uint32_t& r3) {
  asm volatile("ldmatrix.sync.aligned.m8n8.x4.shared.b16 {%0,%1,%2,%3}, [%4];" : "=r"(r0), "=r"(r1), "=r"(r2), "=r"(r3) : "r"(a) : "memory");
}
__device__ __forceinline__ void ldsm4t(uint32_t a, uint32_t& r0, uint32_t& r1, uint32_t& r2, uint32_t& r3) {
  asm volatile("ldmatrix.sync.aligned.m8n8.x4.trans.shared.b16 {%0,%1,%2,%3}, [%4];" : "=r"(r0), "=r"(r1), "=r"(r2), "=r"(r3) : "r"(a) : "memory");
}
__device__ __forceinline__ void hmma(float* d, uint32_t a0, uint32_t a1, uint32_t a2, uint32_t a3, uint32_t b0, uint32_t b1) {
  asm volatile("mma.sync.aligned.m16n8k16.row.col.f32.bf16.bf16.f32 {%0,%1,%2,%3}, {%4,%5,%6,%7}, {%8,%9}, {%0,%1,%2,%3};"
               : "+f"(d[0]), "+f"(d[1]), "+f"(d[2]), "+f"(d[3]) : "r"(a0), "r"(a1), "r"(a2), "r"(a3), "r"(b0), "r"(b1));
}
__device__ __forceinline__ void stg32_if(bool on, void* p, uint32_t v) {
  asm volatile("{\n.reg .pred p;\nsetp.ne.b32 p, %2, 0;\n@p st.global.u32 [%0], %1;\n}" ::"l"(p), "r"(v), "r"((int)on) : "memory");
}
__device__ __forceinline__ void ldg128_if(bool on, const void* p, uint32_t* v) {
  asm volatile("{\n.reg .pred p;\nsetp.ne.b32 p, %5, 0;\n@p ld.relaxed.gpu.global.v4.u32 {%0,%1,%2,%3}, [%4];\n}" : "=r"(v[0]), "=r"(v[1]), "=r"(v[2]), "=r"(v[3]) : "l"(p), "r"((int)on) : "memory");
}
__device__ __forceinline__ void lds32_if(bool on, uint32_t& v, uint32_t a) {
  asm volatile("{\n.reg .pred p;\nsetp.ne.b32 p, %2, 0;\n@p ld.shared.u32 %0, [%1];\n}" : "=r"(v) : "r"(a), "r"((int)on) : "memory");
}
__device__ __forceinline__ void st_peer4(uint32_t ra, const uint4* v, uint32_t rbar) {
#define SP(o, a, b, c, d) "st.async.weak.shared::cluster.mbarrier::complete_tx::bytes.v4.b32 [%0+" #o "], {%" #a ",%" #b ",%" #c ",%" #d "}, [%1];\n"
  asm volatile(SP(0, 2, 3, 4, 5) SP(512, 6, 7, 8, 9) SP(1024, 10, 11, 12, 13) SP(1536, 14, 15, 16, 17)
               ::"r"(ra), "r"(rbar), "r"(v[0].x), "r"(v[0].y), "r"(v[0].z), "r"(v[0].w), "r"(v[1].x), "r"(v[1].y), "r"(v[1].z), "r"(v[1].w),
                 "r"(v[2].x), "r"(v[2].y), "r"(v[2].z), "r"(v[2].w), "r"(v[3].x), "r"(v[3].y), "r"(v[3].z), "r"(v[3].w) : "memory");
}
__device__ __forceinline__ uint32_t ldg32(const void* p) { uint32_t v; asm volatile("ld.global.nc.u32 %0, [%1];" : "=r"(v) : "l"(p)); return v; }
__device__ __forceinline__ uint32_t ldg16(const void* p) { uint16_t v; asm volatile("ld.global.nc.u16 %0, [%1];" : "=h"(v) : "l"(p)); return v; }
__device__ __forceinline__ uint32_t pack2(float lo, float hi) { uint32_t d; asm("cvt.rn.bf16x2.f32 %0, %1, %2;" : "=r"(d) : "f"(hi), "f"(lo)); return d; }
__device__ __forceinline__ float blo(uint32_t x) { return __uint_as_float(x << 16); }
__device__ __forceinline__ float bhi(uint32_t x) { return __uint_as_float(x & 0xffff0000u); }
__device__ __forceinline__ float bround(float x) { return bhi(pack2(0.f, x)); }
__device__ __forceinline__ uint32_t bmul2(uint32_t a, uint32_t b) { uint32_t d; asm("mul.rn.bf16x2 %0, %1, %2;" : "=r"(d) : "r"(a), "r"(b)); return d; }
__device__ __forceinline__ uint32_t badd2(uint32_t a, uint32_t b) { uint32_t d; asm("add.rn.bf16x2 %0, %1, %2;" : "=r"(d) : "r"(a), "r"(b)); return d; }
__device__ __forceinline__ uint32_t bfma2(uint32_t a, uint32_t b, uint32_t c) { uint32_t d; asm("fma.rn.bf16x2 %0, %1, %2, %3;" : "=r"(d) : "r"(a), "r"(b), "r"(c)); return d; }
__device__ __forceinline__ float silu(float x) { return __fdividef(x, 1.f + __expf(-x)); }
__device__ __forceinline__ float gelu2(float a, float k1, float k2) {
  float u, t;
  asm volatile("mul.rn.f32 %0, %1, %1;" : "=f"(u) : "f"(a));
  asm("tanh.approx.f32 %0, %1;" : "=f"(t) : "f"(a * fmaf(u, k2, k1)));
  asm volatile("fma.rn.f32 %0, %0, %1, %0;" : "+f"(a) : "f"(t));
  return a;
}
__device__ __forceinline__ void stage_end() { asm volatile("pmevent 1;"); }
__device__ __forceinline__ uint32_t bdup(uint32_t x, int hi) {
  uint32_t d;
  if (hi) asm("{\n.reg .b16 l, h;\nmov.b32 {l, h}, %1;\nmov.b32 %0, {h, h};\n}" : "=r"(d) : "r"(x));
  else asm("{\n.reg .b16 l, h;\nmov.b32 {l, h}, %1;\nmov.b32 %0, {l, l};\n}" : "=r"(d) : "r"(x));
  return d;
}
__device__ __forceinline__ uint32_t baffine(uint32_t x, uint32_t c) {
  uint32_t d;
  asm("{\n.reg .b16 l, h;\n.reg .b32 a, b;\nmov.b32 {l, h}, %2;\nmov.b32 a, {l, l};\nmov.b32 b, {h, h};\nfma.rn.bf16x2 %0, %1, a, b;\n}" : "=r"(d) : "r"(x), "r"(c));
  return d;
}
__device__ __forceinline__ uint32_t clk32() { uint32_t t; asm volatile("mov.u32 %0, %%clock;" : "=r"(t)::"memory"); return t; }
__device__ __forceinline__ void sleep_until(uint32_t t0) {
  asm volatile("{\n.reg .pred p;\n.reg .s32 t;\nSL:\nmov.u32 t, %%clock;\nsub.s32 t, t, %0;\nsetp.lt.s32 p, t, 0;\n@p nanosleep.u32 20;\n@p bra.uni SL;\n}" ::"r"(t0) : "memory");
}
__device__ __forceinline__ void sleep_for(uint32_t d) { sleep_until(__shfl_sync(0xffffffffu, clk32() + d + (threadIdx.x & 31), 0)); }

#define TSP(mask, on, id) do {} while (0)
#define TSX(mask, id) do {} while (0)
#define TGX(id) do {} while (0)
#define FX(id) do {} while (0)
#define TS1(id) TSX(1, id)
#define TS2(id) TSX(2, id)
#define TS3(id) TSX(4, id)
#define TSS(id) TSX(7, id)
#define W0(id) (w == 0 ? (id) : 127)

template <int N>
__device__ __forceinline__ void bfly(float* v, int lane, int mask) {
  const bool b = lane & mask;
#pragma unroll
  for (int i = 0; i < N / 2; i++) {
    float mine = b ? v[i + N / 2] : v[i], other = b ? v[i] : v[i + N / 2];
    v[i] = mine + __shfl_xor_sync(0xffffffffu, other, mask);
  }
}
__device__ __forceinline__ float quad_sum(float x) { x += __shfl_xor_sync(0xffffffffu, x, 1); return x + __shfl_xor_sync(0xffffffffu, x, 2); }

template <int N>
__device__ __forceinline__ void conv_tri(float* acc, uint32_t (*A)[4], uint64_t db) {
  if constexpr (N == 128) wrs128_first(acc, A[0], db); else WRS<N>::mma(acc, A[0], db);
  if constexpr (N > 16) conv_tri<N - 16>(acc, A + 1, db + 16);
}
__device__ __forceinline__ void conv_mma(float* acc, uint32_t (*A)[4], uint64_t db) {
  WG_FENCE();
  conv_tri<128>(acc, A + 8, db + 128);
  WG_COMMIT();
  WG_FENCE();
  WRS<128>::mma(acc, A[7], db + 112); WRS<128>::mma(acc, A[6], db + 96);
  WG_COMMIT();
  WG_WAIT(1);
  WG_FENCE();
  conv_tri<128>(acc + 64, A, db + 128);
#pragma unroll
  for (int T = 5; T >= 0; T--) WRS<128>::mma(acc, A[T], db + 16 * T);
  WG_COMMIT();
}
template <int N>
__device__ __forceinline__ void zero_acc(float* a) {
#pragma unroll
  for (int i = 0; i < N; i += 2) asm volatile("mov.b64 {%0, %1}, 0;" : "=f"(a[i]), "=f"(a[i + 1]));
}
template <int N>
__device__ __forceinline__ void undef(float* a) {
#pragma unroll
  for (int i = 0; i < N; i++) asm volatile("" : "=f"(a[i]));
}
__device__ __forceinline__ uint32_t ext_frag(float mu, float sg, int q) {
  const float mh = bround(-mu), sh = bround(sg);
  const float lo = q == 0 ? mh : q == 1 ? -mu - mh : sh, hi = q == 0 ? mh : q == 1 ? sh : sg - sh;
  return pack2(lo, hi) & (q == 3 ? 0u : ~0u);
}
__device__ __forceinline__ uint32_t opaque(uint32_t x) { asm volatile("" : "+r"(x)); return __shfl_sync(0xffffffffu, x, 0); }
__device__ __forceinline__ uint32_t tagw(uint32_t x, uint32_t par) { return (x & ~1u) | par; }
__device__ __forceinline__ uint32_t bitsel(uint32_t x, uint32_t y, uint32_t mask) { return (x & ~mask) | (y & mask); }
__device__ __forceinline__ uint32_t stale(uint32_t acc, uint32_t x, uint32_t par) { uint32_t d; asm("lop3.b32 %0, %1, %2, %3, 0xf6;" : "=r"(d) : "r"(acc), "r"(x), "r"(par)); return d; }
__device__ __forceinline__ bool any_stale(uint32_t acc) { return __builtin_expect(__any_sync(0xffffffffu, acc & 1), 0); }
__device__ __forceinline__ uint32_t sum2(uint32_t a, uint32_t b, uint32_t c, uint32_t d) { return pack2(__uint_as_float(a) + __uint_as_float(b), __uint_as_float(c) + __uint_as_float(d)); }
__device__ __forceinline__ void refetch(uint32_t ta, const uint4* gp, uint32_t wo, uint32_t par) {
  bool again;
#pragma unroll 1
  do { again = any_stale(lds32(ta + wo) ^ par); sts128(ta, ld_relaxed4(gp)); sts128(ta + 16, ld_relaxed4(gp + 1)); } while (again);
  fence_async_s();
}

__global__ void __cluster_dims__(2, 1, 1) __launch_bounds__(512, 1)
fused_kernel(const __grid_constant__ Params p, const __grid_constant__ Maps tm) {
  extern __shared__ __align__(1024) unsigned char smem_raw[];
  const uint32_t tstart = __shfl_sync(0xffffffffu, clk32() + (threadIdx.x & 31), 0);
  const uint32_t sb = __shfl_sync(0xffffffffu, (uint32_t)__cvta_generic_to_shared(smem_raw), 0);
  const int tid = threadIdx.x, lane = tid & 31;
  const int warp = __shfl_sync(0xffffffffu, tid >> 5, 0);
  const int wg = warp >> 2, w = warp & 3, t128 = tid & 127;
  const int r = lane >> 2, q = lane & 3, mi = lane >> 3, rr = lane & 7;
  Scratch* const G = p.g;
  auto BAR = [&](int i) { return sb + SM_BAR + i * 8; };
  if (warp == 15) asm volatile("{\n.reg .u32 t;\nld.relaxed.gpu.global.u32 t, [%0];\nshr.u32 t, t, 6;\nredux.sync.min.u32 t, t, 0xffffffff;\nadd.u32 t, t, 1;\nst.shared.u32 [%1], t;\n}"
                               ::"l"(G->cnt + min(lane, C_E + 1) * 32), "r"(sb + SM_TPC + 4) : "memory");
  unsigned crank, mytpc;
  asm("mov.u32 %0, %%smid;" : "=r"(mytpc));
  asm("mov.u32 %0, %%cluster_ctarank;" : "=r"(crank));
  mytpc = (p.by_sm ? mytpc : blockIdx.x) >> 1;
  const int bid = (mytpc < 60 ? mytpc : mytpc < 62 ? mytpc + 4 : mytpc - 2) * 2 + crank;
  if (wg == 1) asm volatile("barrier.cluster.arrive.relaxed.aligned;" ::: "memory");
  if (warp >= 4 && warp < 10 && bid < 128) {
    const int i = warp < 8 ? warp - 2 : warp - 8, it = (int)(SEQ0 >> (8 * i)), s = it & 15;
    const __nv_bfloat16* a = (&p.k)[(it >> 4) & 3] + ((it & 32) ? (s * 128 + bid) * 2048 + lane * 64 : ((bid >> 1) * 32 + lane) * 640 + s * 128 + crank * 64);
    if (i > 2) asm volatile(ELECT "prefetch.tensormap [%0];\n}" ::"l"(&tm.k + (5 - i)) : "memory");
    if (i > 1) sleep_until(tstart + T_2 - 2 * PACE_D + i * PACE_D);
    asm volatile("prefetch.global.L2 [%0];" ::"l"(a));
  }
#define BI(o) "@e mbarrier.init.shared::cta.b64 [%0+" #o "], %1;\n"
  if (warp == 12 && bid < 128) {
    asm volatile("{\n.reg .pred e;\nelect.sync _|e, 0xffffffff;\n" BI(0) "fence.mbarrier_init.release.cluster;\n}" ::"r"(BAR(B_KV)), "r"(1) : "memory");
    w_expect(BAR(B_KV), 11520 + 5120);
    tma5d(sb, &tm.k, crank * 64, 0, (bid >> 1) * 4 - 1, 0, BAR(B_KV));
    tma5d(sb + KV_V, &tm.v, crank * 64, 0, (bid >> 1) * 4, 0, BAR(B_KV));
    bulk_g2s(sb + SM_S, p.shiftk, 5120, BAR(B_KV));
  }
  if (warp < 4) {
#pragma unroll 1
    for (int g = warp; g < 16; g += 4)
      asm volatile("{\n.reg .pred e;\nelect.sync _|e, 0xffffffff;\n" BI(8) BI(16) BI(24) BI(32) BI(40) BI(48) BI(56) "fence.mbarrier_init.release.cluster;\n}"
                   ::"r"(BAR(g * 7)), "r"(g < 7 ? (bid >= 128 && !g ? 14 : 1) : g < 9 ? 2 : 4) : "memory");
  }
  if (tid == 96) sts32(sb + SM_TPC, mytpc);
  if (wg != 1) asm volatile("barrier.cluster.arrive.relaxed.aligned;" ::: "memory");
  auto READY = [&]() { asm volatile("barrier.cluster.wait.aligned;" ::: "memory"); };
  auto EPOCH = [&]() { return lds32(sb + SM_TPC + 4); };

  if (bid >= 128) {
    const int j = bid - 128;
    READY();
    constexpr uint32_t S_TAB = SM_S;
    if (warp < 14) {
      const unsigned tag = EPOCH(), par = tag & 1;
      const uint32_t to = sb + S_TAB + (tid >> 2) * 64 + q * 8;
      st_relaxed4(G->vt + (tid < 224 ? j * 224 : (3 + j) * 224) + tid, make_uint4(0, 0, 0, (tag - 1) & 0x3fff));
      if (tid < 192 && j * 192 + tid < 640) st_relaxed(G->gb + j * 192 + tid, par ^ 1);
      if (tid < 160) {
        const uint32_t c0 = ldg32(p.c + (tid >> 2) * 16 + q * 2), c1 = ldg32(p.c + (tid >> 2) * 16 + q * 2 + 8);
        sts64(to + 4096, pack2(silu(blo(c0)), silu(bhi(c0))), pack2(silu(blo(c1)), silu(bhi(c1))));
        sleep_until(tstart + 9000);
        wait_cnt(G->cnt + (C_M + (lane & 1)) * 32, tag * 64u);
        const uint4* mp = (const uint4*)(G->modp + 1920) + tid;
        uint4 a, b, c, d;
#pragma unroll 1
        do {
          a = ld_relaxed4(mp); b = ld_relaxed4(mp + 800); c = ld_relaxed4(mp + 160); d = ld_relaxed4(mp + 960);
        } while (any_stale(stale(stale(stale(a.x ^ par, b.x, par), c.x, par), d.x, par)));
        sts64(to, badd2(sum2(c.x, d.x, c.z, d.z), 0x3f803f80), badd2(sum2(c.y, d.y, c.w, d.w), 0x3f803f80));
        sts64(to + 32, sum2(a.x, b.x, a.z, b.z), sum2(a.y, b.y, a.w, b.w));
      }
      bar_sync(1, 448);
      TSS(warp == 0 ? 10 : 127);
            int st = 0, ph = 0;
#pragma unroll 1
      for (int part = 0; part < 3; part++) {
        float d[2][4] = {{0.f, 0.f, 0.f, 0.f}, {0.f, 0.f, 0.f, 0.f}};
        const int ch = 2 * warp + (mi & 1) + (part < 2 && part == (j == 1) ? 4 : 0);
        const uint32_t ao = sb + (ch >> 3) * 8192 + (rr + (mi >> 1) * 8) * 128 + (((ch & 7) ^ rr) << 4);
#pragma unroll 1
        for (int u = 0; u < 10; u++) {
          uint32_t a[4][4];
          uint2 b[4];
#pragma unroll
          for (int i = 0; i < 4; i++) b[i] = lds64(sb + S_TAB + (part >> 1) * 4096 + (u * 4 + i) * 64 + (r & 1) * 32 + q * 8);
          mbar_wait(BAR(B_FULL1 + st), ph);
#pragma unroll
          for (int i = 0; i < 4; i++) ldsm4t(ao + st * 32768 + i * 2048, a[i][0], a[i][1], a[i][2], a[i][3]);
#pragma unroll
          for (int i = 0; i < 4; i++) hmma(d[i & 1], a[i][0], a[i][1], a[i][2], a[i][3], b[i].x, b[i].y);
          w_arrive(BAR(1 + st));
          if (++st == 6) { st = 0; ph ^= 1; }
        }
#pragma unroll
        for (int i = 0; i < 2; i++) {
          const float a = d[0][2 * i] + d[1][2 * i], b = d[0][2 * i + 1] + d[1][2 * i + 1], ah = bround(a), bh = bround(b);
          const int cc = warp * 16 + i * 8 + r;
          if (q == 0 && part < 2) st_relaxed4(G->vt + (part * 4 + j) * 224 + cc, make_uint4(pack2(ah, a - ah), pack2(ah, bh), pack2(b - bh, bh), tag & 0x3fff));
          if (q == 0 && part == 2 && cc < 192 && j * 192 + cc < 640) st_relaxed(G->gb + j * 192 + cc, __float_as_uint(ah) | par);
        }
        TSS(warp == 0 ? 1 + part : 127);
      }
    } else if (warp == 14) {
      sleep_until(tstart + T_SPARE);
      uint32_t fb = BAR(B_FULL1), dst = sb, ph = 1;
#pragma unroll 1
      for (int part = 0; part < 3; part++) {
        const int c0 = part == 2 ? 50 + j * 3 : ((part ? 0 : 864) + nstart(j)) >> 6;
#pragma unroll 1
        for (int row = 0; row < 640; row += 64) {
          mbar_wait(fb - (B_FULL1 - 1) * 8, ph);
#pragma unroll 1
          for (int x = 0; x < 2; x++) { w_expect(fb, 16384); tma3d(dst + x * 16384, part == 2 ? &tm.wm2 : &tm.w2, 0, row, c0 + x * 2, fb); }
          fb += 8; dst += 32768;
          if (dst == sb + 196608) { fb -= 48; dst = sb; ph ^= 1; }
        }
      }
    } else {
      const unsigned tag = EPOCH();
#pragma unroll 1
      for (int spin = 0; __any_sync(0xffffffffu, (int)(ld_relaxed(G->cnt + (C_E + (lane & 1)) * 32) - tag * 64u) < 0); spin++) { if (spin > (1 << 18)) __trap(); __nanosleep(500); }
    }
    return;
  }
  const int m = p.tile[bid >> 1] >> 1, n = (p.tile[bid >> 1] & 1) * 2 + crank;
  const uint32_t peer = mapa(sb, crank ^ 1) - sb;

  unsigned tag = 0, par = 0;
  if (wg == 3) {
    asm volatile("setmaxnreg.dec.sync.aligned.u32 32;");
    auto pf_wsp = [&](int i) {
      const __nv_bfloat16* a = p.wsp + ((m >> 1) * 128 + (m & 1) * 32 + lane) * 2048 + ((i + ROT * (m >> 3)) & 15) * 128 + (i >> 4) * 64;
      asm volatile("prefetch.global.L2 [%0];\nprefetch.global.L2 [%0+262144];" ::"l"(a));
    };
    if (w == 3) {
      READY();
      TS1(103);
      const unsigned tag = EPOCH();
      TS1(100);
      if (lane < 9) mbar_expect(BAR(B_AP + lane), lane < 5 ? 8192 : lane < 7 ? (lane - 4) * 1024 : 14336);
      if (lane < 10) mbar_expect(BAR(B_U + lane), lane < 5 ? 4096 : 8192);
#pragma unroll 1
      for (int s = 0; s < 5; s++) {
        if (s && lane < 2) tmap_prefetch(&tm.wm + 2 * s - 2 + lane);
        mbar_wait(BAR(s < HINT_A ? B_KV + s : B_KVF + s), 0);
        if (s < NAPS) sleep_for(NAPA);
        wait_cnt(G->cnt + (C_A + 2 * s + (bid >> 6)) * 32, tag * 64u);
        bulk_g2s(sb + offU(s), G->T + (s * 128 + bid) * 256, 4096, BAR(B_U + s));
        TS1(80 + s);
      }
      {
        uint32_t t;
        asm volatile("ld.shared::cluster.u32 %0, [%1];" : "=r"(t) : "r"(sb + SM_TPC + peer) : "memory");
        if (t != mytpc) __trap();
        unsigned todo = 31;
        mbar_wait(BAR(B_WMF), 0);
#pragma unroll 1
        do {
          unsigned rdy = __ballot_sync(0xffffffffu, ((todo >> lane) & 1) && (int)(ld_relaxed(G->cnt + (C_Y + 2 * lane + crank) * 32) - tag * 64u) >= 0);
          todo &= ~rdy;
#pragma unroll 1
          for (; rdy; rdy &= rdy - 1) {
            const int s = __ffs(rdy) - 1;
            tma3d(sb + s * 16384 + (crank ^ 1) * 8192, &tm.y, 0, s * 128 + crank * 64, m * 2, BAR(B_YH + s));
            TS1(85 + s);
          }
        } while (todo);
      }
#pragma unroll 1
      for (int part = 0; part < 2; part++) {
        const uint4* vp = G->vt + (part * 4 + n) * 224;
        if (STOP_AFTER >= 2) mbar_wait2(BAR(part ? B_VTF : B_AO), BAR(B_AO + 1 + H2), 0, 0);
#pragma unroll 1
        while (__any_sync(0xffffffffu, ld_relaxed(&vp[223].w) != (tag & 0x3fff))) {}
        unsigned bad, ph = 1;
#pragma unroll 1
        do {
          w_expect(BAR(B_U + part), 3584); bulk_g2s(sb + (STOP_AFTER >= 2 ? SM_VT : SM_X1), vp, 3584, BAR(B_U + part));
          mbar_wait(BAR(B_U + part), ph);
          ph ^= 1; bad = 0;
#pragma unroll
          for (int k = 0; k < 7; k++) bad |= lds32(sb + (STOP_AFTER >= 2 ? SM_VT : SM_X1) + k * 512 + lane * 16 + 12) ^ tag;
        } while (__any_sync(0xffffffffu, bad & 0x3fff));
        w_arrive(BAR(B_VT));
        TS2(75 + part);
      }
      if (STOP_AFTER >= 2) {
        pf_wsp(20 + n);
        mbar_wait2(BAR(B_PUB), BAR(B_X1D), 0, 0);
#pragma unroll 1
        for (int h = 0; h < 2; h++) {
          if (h) { fence_async_g(); fence_gpu(); }
          w_count(G, C_H + 2 * h + crank);
          TS2(77 + h);
          pf_wsp(24 + 4 * h + n);
          sleep_for(POLL1);
#pragma unroll 1
          while (__any_sync(0xffffffffu, (int)(ld_acquire(G->cnt + (C_H + 2 * h + (lane & 1)) * 32) - tag * 64u) < 0)) {}
          w_arrive(BAR(B_LOK + 1 + h));
          TS2(91 + h);
        }
        fence_async_g();
        if (lane == 0) asm volatile("cp.async.bulk.prefetch.L2.global [%0], 8640;" ::"l"(p.wout + bid * 4320) : "memory");
      }
      if (STOP_AFTER >= 4) {
#pragma unroll 1
        for (int s = 0; s < 5; s++) {
          uint2 a;
#pragma unroll 1
          for (;;) { a = ld_relaxed2(G->gb + s * 128 + crank * 64 + lane * 2); if (!any_stale(stale(a.x ^ tag, a.y, tag))) break; __nanosleep(200); }
          sts32(sb + SM_GB + s * 128 + (r >> 2) * 64 + q * 16 + (r & 3) * 4, __byte_perm(a.x, a.y, 0x7632));
        }
        w_arrive(BAR(B_GB));
      }
      goto done;
    }
    if (w == 2) {
      const uint32_t dsk = ldg16(p.ssmD + min(lane, 4) * 128 + bid);
      READY();
#pragma unroll 1
      for (int s = 0; s < 5; s++) {
        const uint32_t fE = sb + offF(s) + 16 + lane * 16, dk = __shfl_sync(0xffffffffu, dsk, s);
        mbar_wait(BAR(B_F + s), 0);
        TSX(17, 70 + s);
#pragma unroll 1
        for (int o = 2048; o >= 0; o -= 2048) {
          uint4 e[4];
          uint32_t nx[4];
#pragma unroll
          for (int i = 0; i < 4; i++) { e[i] = lds128(fE + o + i * 512); nx[i] = lds32(fE + o + i * 512 + 16); }
          if (lane + o == 0) { const uint32_t f0 = pack2(blo(e[0].x) + blo(dk), bhi(e[0].x)); sts32(fE, f0); sts32(fE + 4156, f0 << 16); }
#pragma unroll
          for (int i = 0; i < 4; i++) sts128(fE + o + 4160 + i * 512, make_uint4(__byte_perm(e[i].x, e[i].y, 0x5432), __byte_perm(e[i].y, e[i].z, 0x5432), __byte_perm(e[i].z, e[i].w, 0x5432), __byte_perm(e[i].w, nx[i], 0x5432)));
        }
        asm volatile(ELECT "mbarrier.arrive.shared::cta.b64 _, [%0], 4;\n}" ::"r"(BAR(B_FO + s)) : "memory");
        TS1(75 + s);
      }
    }
    if (w < 2) {
      {
        const int it = (int)(((lane < 8 ? SEQ0 : lane < 16 ? SEQ1 : lane < 24 ? SEQ2 : SEQ3) >> (8 * rr)) & 255), ty = it >> 4, s = it & 15;
        const bool on = lane < 25 && (ty != 3 || bid < 100);
        const uint32_t bi = ty == 4 ? B_Q + (s > 2) : max(ty - 1, 0) * 5 + s;
        const uint32_t a0 = ty == 3 ? (bid >> 1) * 64 + ((crank * 320 + s * 64) << 16) : ty == 2 ? 0 : s * 128 + crank * 64;
        const uint32_t a1 = ty < 2 ? ((bid >> 1) * 4 - 1 + ty) << 8 : ty == 2 ? (s * 128 + bid) << 8 : ty == 3 ? 0 : ((m & ~1) << 8) + (m & 1) * 4;
        const uint32_t a2 = (ty == 2 ? offF(s) + 16 : s * 16384 + (ty < 2 ? ty * KV_V : ((ty ^ crank) & 1) * 8192)) + ty + (bi << 18) + ((B_KVF + s) << 24);
        const uint32_t a3 = tstart + T_2 - 2 * PACE_D + lane * PACE_D + max(lane - 13, 0) * (PACE_F - PACE_D) + min(max(lane - WPOS, 0), 5) * (PACE_W - PACE_F) + max(lane - 20, 0) * (PACE_Q - PACE_F);
        unsigned todo = __ballot_sync(0xffffffffu, on) & (0x55555555u << (2 + w));
        READY();
        if (on && ty != 1 && (it <= 0x40 || it == 0x44) && lane && !w) mbar_expect(BAR(bi), ty == 0 ? 11520 : ty == 2 ? 4096 : ty == 3 ? 8192 : 24576 - s * 2048);
#pragma unroll 1
        while (todo) {
          const int i = __ffs(todo) - 1;
          const uint32_t b0 = __shfl_sync(0xffffffffu, a0, i), b1 = __shfl_sync(0xffffffffu, a1, i), b2 = __shfl_sync(0xffffffffu, a2, i);
          todo &= todo - 1;
          sleep_until(__shfl_sync(0xffffffffu, a3, i));
          TSX(16, 1 + i);
          if ((b2 & 7) > 2) mbar_wait(BAR(b2 >> 24), 0);
          tma5d(sb + (b2 & 0x3ff80), &tm.k + (b2 & 7), b0 & 0xffff, b0 >> 16, (int)b1 >> 8, b1 & 255, BAR((b2 >> 18) & 63));
        }
      }
      TS1(w == 0 ? 95 : 127);
    }
    if (w) {
      const int x = w - 1;
      if (STOP_AFTER >= 2) {
        sleep_until(tstart + T_WIN);
#pragma unroll 1
        for (int g = 0; g < 20; g++) {
          const int base = (g < 10 ? 864 : 0) + nstart(n), row = ((g < 10 ? g : g - 10) ^ crank) * 64;
          const uint32_t fb = BAR(B_FULL1 + (g & 3)), dst = sb + SM_R + (g & 3) * 32768;
          mbar_wait(fb + (B_EMPTY1 - B_FULL1) * 8, (g >> 2) & 1);
          w_expect(fb, 16384); tma3d(dst + x * 16384, &tm.w2, 0, row, (base >> 6) + x * 2, fb);
        }
      }
    } else {
      const unsigned tag = lds32(sb + SM_TPC + 4);
      mbar_wait(BAR(B_WMF), 0);
      if (NAPM) sleep_for(NAPM);
      wait_cnt(G->cnt + (C_M + (lane & 1)) * 32, tag * 64u);
      w_arrive(BAR(B_YH + 5));
      TS1(90);
      if (STOP_AFTER >= 2) {
#pragma unroll 1
        for (int s = 0; s < 5; s++) {
          mbar_wait(BAR(B_AO + s), 0);
          tma5d_store(&tm.x1, s * 128 + crank * 64, m & ~1, (m & 1) * 4 + (n & 2), sb + SM_X1 + (s & 1) * 4096);
          bulk_commit();
          pf_wsp(4 * s + n);
          bulk_wait_read0();
          w_arrive(BAR(B_XF + (s & 1)));
        }
        asm volatile("cp.async.bulk.wait_group 0;" ::: "memory");
        w_arrive(BAR(B_X1D));
      }
      if (STOP_AFTER >= 3) {
        mbar_wait(BAR(B_VTF), 0);
        sleep_for(POLL0);
        TS2(100);
        uint4 c;
#pragma unroll 1
        do c = ld_relaxed4(G->cnt + (C_G + (lane & 1)) * 32); while (__any_sync(0xffffffffu, (int)(c.x - tag * 64u) < 0));
        TS2(101);
#pragma unroll 1
        for (;;) {
          uint32_t t;
          asm volatile("mov.u32 %0, %%globaltimer_lo;" : "=r"(t)::"memory");
          if (__all_sync(0xffffffffu, t - c.z >= DELAY0)) break;
        }
        w_arrive(BAR(B_LOK));
      }
    }
    if (STOP_AFTER >= 3) {
      const uint4* zp = G->z2n + n * 32 * IMG;
      uint32_t off = 0, ph = 0;
      mbar_wait(BAR(w == 1 ? B_X1D : B_LOK), 0);
#pragma unroll 1
      for (int i = 0; i < 32; i++) {
        const int M = (i + ROT * (m >> 3)) & 15;
        const uint32_t fb = BAR(B_FULL2) + off, dst = sb + (((uint32_t)((w == 1 ? 0x40906C1CD8ull : 0x9874245000ull) >> off) & 255) << 10);
        if (i == 16) mbar_wait(BAR(B_LOK + 1), 0);
        mbar_wait(fb + (B_EMPTY2 - B_FULL2) * 8, ph);
        if (!w) { if (i < 10 || i == 16) TS2(min(80 + i, 90)); if (i < 15) TSX(8, 81 + i); }
        if (w == 1) { if (i < 15) TSX(8, 101 + i); w_expect(fb, 8192); tma_rows(dst, &tm.wsp, M * 128 + (i >> 4) * 64, m & ~1, (m & 1) * 4, fb); }
        else if ((i & 1) * 2 == w) { w_expect(fb, 28672); bulk_g2s(dst, zp + ((i & 16) + M) * IMG, 28672, fb); }
        off += 8;
        if (off == 40) { off = 0; ph ^= 1; }
      }
    }
    if (w) {
      const int x = w - 1;
      if (STOP_AFTER >= 4) {
#pragma unroll 1
        for (int k = 0; k < 10; k++) {
          const int st = 1 + ((k + 1) & 3);
          const uint32_t fb = BAR(B_FULL2 + st);
          mbar_wait(fb + (B_EMPTY2 - B_FULL2) * 8, ((k + 1) >> 2) & 1);
          TS3(x ? 127 : 60 + k);
          w_expect(fb, 14336);
          tma2d(sb + placeB(st) + x * 14336, &tm.wo, (k < 8 ? (k & 2) + x : 4) * 128 + crank * 64, nstart(n ^ (k < 8 ? k >> 2 : k & 1)) + 112 * (k < 8 ? k & 1 : x), fb);
        }
      }
    } else {
      if (STOP_AFTER >= 4) mbar_wait(BAR(B_GB), 0);
      w_count(G, C_E + crank);
      if (STOP_AFTER >= 4) {
        mbar_wait_b(BAR(B_PFREE), 0);
#pragma unroll 1
        for (int e = 0; e < 2; e++) {
          mbar_wait_b(BAR(B_PST + max(e, PONE)), 0);
          if (e) { mbar_wait_b(BAR(B_EMPTY2 + PGATE), 1); sleep_for(100); }
          bulk_s2peer(sb + e * 14336 + peer, sb + SM_PO + e * 14336, 14336, BAR(B_PP + e) + peer);
        }
        mbar_wait_b(BAR(B_PP), 0);
        TS3(24);
        mbar_wait_b(BAR(B_PP + 1), 0);
        TS3(25);
        w_arrive_peer(BAR(B_ACK) + peer);
        mbar_wait_b(BAR(B_ACK), 0);
      }
      w_arrive(BAR(B_DONE + 3));
#pragma unroll 1
      for (int i = 3; i >= 0; i--) mbar_wait_b(BAR(B_DONE + i), 0);
      return;
    }
    goto done;
  }
  if (wg < 2) {
    sleep_until(tstart + T_AB);
    asm volatile("setmaxnreg.inc.sync.aligned.u32 192;");
    READY();
    tag = EPOCH(); par = tag & 1;
    {
      const uint32_t lofs = (r & 1) ? (16 + 4 * (4 * w + ((r - 1) >> 1) - q)) : (16 + 4160 + 4 * (4 * w + (r >> 1) - 1 - q));
      const uint32_t pl = sb + SM_R + (5 + 2 * wg) * 16384, pa = pl + w * 4096 + ((255 - lane) ^ ((~lane & 8) >> 1)) * 16;
      uint32_t pg[4];
#pragma unroll
      for (int i = 0; i < 4; i++) { const uint32_t x = ((t128 & 112) + (lane & 1) * 8 + ((lane & 15) >> 1) - i) & 255; pg[i] = (x ^ ((x & 8) >> 1)) * 16; }
      if (lane < w) sts128(pa, make_uint4(0, 0, 0, 0));
      if (2 * w < 4 + wg) {
        const uint32_t ub = sb + offU(2 * w + 1 - wg);
        sts32(ub + 4096 + lane * 4, 0);
        if (lane < 3) sts32(ub + 8368 + lane * 4, 0);
      }
      if (warp == 7) sts32(sb + SM_ONE + lane * 4, 0x3f803f80);
      if (tid < 160) { const uint32_t c = ldg32(p.c + crank * 320 + tid * 2); sts32(sb + SM_SILU + tid * 4, pack2(silu(blo(c)), silu(bhi(c)))); }
      fence_async_s();
      bar_sync(6, 256);
      if (!wg) {
        w_arrive(BAR(B_MT));
        if (q < 2) st_relaxed2(G->st3 + ((m * 4 + n) * 2 + q) * 32 + w * 8 + r, par ^ 1, 0);
      }
      const uint32_t p0 = lane < w ? sb + SM_DUMMY + lane * 16 : pa, uo = t128 * 32 + r * 4;
      uint4* yp = G->Y + ((1 - wg) * 128 + bid) * 256 + t128;
      uint32_t A[16][4];
      auto frag = [&](bool on, uint32_t fa, int T) {
#pragma unroll
        for (int i = 0; i < 4; i++) lds32_if(on, A[T][i], fa + T * 256 + (i & 1) * 128 + (i & 2) * 32);
      };
      mbar_wait(BAR(B_FO + 1 - wg), 0);
#pragma unroll
      for (int T = 0; T < 16; T++) frag(true, sb + offF(1 - wg) + lofs, T);
#pragma unroll 1
      for (int s = 1 - wg;; s += 2) {
        float acc[128];
        const uint32_t ub = sb + offU(s), fa = sb + offF(s + 2) + lofs;
        mbar_wait(BAR(B_U + s), 0);
        const uint32_t ut = lds32(ub + uo);
        if (any_stale(ut ^ par)) { FX(118); refetch(ub + (uo & ~31), G->T + (s * 128 + bid) * 256 + (uo >> 5) * 2, uo & 31, par); }
        if (s) bar_sync(10 + wg, 256); else bar_sync(5, 128);
        TSP(1, w == 0, 10 + s);
        conv_mma(acc, A, mkdesc(ub, 64, 128, 0));
        bar_arrive(11 - wg, 256);
        mbar_wait(BAR(B_FO + min(s + 2, 4)), 0);
        WG_WAIT(0);
        TSP(1, w == 0, 15 + s);
#pragma unroll
        for (int x = 7; x >= 0; x--) {
          frag(s < 3, fa, x);
          uint32_t pk[4];
#pragma unroll
          for (int i = 0; i < 4; i++) {
            const int jj = 4 * x + i;
            float lo = acc[4 * jj], hi = acc[4 * jj + 1];
            if (jj < 31) { lo += acc[4 * jj + 6]; hi += acc[4 * jj + 7]; }
            pk[i] = pack2(lo, hi);
          }
          stsm4t(x ? pa - x * 512 : p0, pk[0], pk[1], pk[2], pk[3]);
        }
        bar_sync(4 + wg, 128);
        TSP(1, w == 0, 20 + s);
        uint4 v[8];
        auto gather = [&]() {
#pragma unroll
          for (int i = 0; i < 8; i++) v[i] = lds128(pl + (i & 3) * 4096 + (pg[i & 3] ^ ((i >> 2) * 2048)));
        };
        auto finish = [&]() {
          if (w == 1) w_count(G, C_Y + 2 * s + (bid >> 6));
#pragma unroll
          for (int e = 0; e < 2; e++) {
            const uint4 a = v[4 * e], b = v[4 * e + 1], c = v[4 * e + 2], d = v[4 * e + 3];
            yp[e * 128] = make_uint4(tagw(badd2(badd2(a.x, b.x), badd2(c.x, d.x)), par), badd2(badd2(a.y, b.y), badd2(c.y, d.y)), badd2(badd2(a.z, b.z), badd2(c.z, d.z)), badd2(badd2(a.w, b.w), badd2(c.w, d.w)));
          }
          yp += 256 * 256;
          w_arrive(BAR(s > 0 ? B_EMPTY1 - 1 + s : B_NIL));
          TSP(1, w == 0, 30 + s);
        };
        if (s >= 3) {
          const int t = min(t128, 64 + (t128 & 15));
          const uint4* mp = (const uint4*)G->modp + (t >> 4) * 32 + crank * 16 + (t & 15);
          uint32_t u[8][4];
          auto fetch = [&](bool on) {
#pragma unroll
            for (int i = 0; i < 8; i++) ldg128_if(on, mp + (i & 1) * 800 + ((i >> 1) + (i >= 6)) * 160, u[i]);
          };
          if (!wg) mbar_wait(BAR(B_YH + 5), 0);
          TSP(1, warp == 0, 61);
          fetch(warp < 3);
          gather();
          finish();
          if (warp < 3) {
#pragma unroll 1
            while (any_stale(stale(stale(stale(u[0][0] ^ par, u[1][0], par), u[2][0], par), u[3][0], par) | stale(stale(stale(u[4][0] ^ par, u[5][0], par), u[6][0], par), u[7][0], par))) fetch(true);
#pragma unroll
            for (int f = 0; f < 4; f += 2) {
              auto sum = [&](int v) { return sum2(u[v][f], u[v + 1][f], u[v][f + 1], u[v + 1][f + 1]); };
              sts128(sb + SM_MOD + (t >> 3) * 256 + (t & 3) * 64 + (t & 4) * 4 + f * 16, make_uint4(bmul2(sum(4), badd2(sum(2), 0x3f803f80)), bmul2(sum(4), sum(0)), badd2(sum(6), 0x3f803f80), 0));
            }
          }
          break;
        }
        gather();
#pragma unroll
        for (int T = 8; T < 16; T++) frag(true, fa, T);
        finish();
      }
    }
    if (!wg) { w_arrive(BAR(B_MT)); TSP(1, w == 0, 63); goto gemm; }
    asm volatile("setmaxnreg.dec.sync.aligned.u32 96;");
  } else {
    asm volatile("setmaxnreg.dec.sync.aligned.u32 96;");
    {
      uint32_t ad[8], mk[4];
#pragma unroll
      for (int x = 0; x < 8; x++) ad[x] = sb + q * 1280 + (((2 * w + (r >> 2)) ^ ((2 * q + x) & 7)) << 4) + (r & 3) * 4;
      const int pc = 255 - (bid >> 1) * 4 - q;
#pragma unroll
      for (int i = 0; i < 4; i++) mk[i] = ((pc >> 3) & 7) == (pc & 1) * 4 + i ? 0x10001u : 0u;
      uint4* d = G->T + (crank * 64 + (t128 >> 2) * 2) * 256 + pc;
      TSP(1, w == 0, 111);
      READY();
      par = EPOCH() & 1;
#pragma unroll 1
      for (int s = 0; s < 5; s++) {
        const uint32_t so = s * 16384;
        mbar_wait(BAR(B_KV + s), 0);
        TSP(1, w == 0, 1 + s); TSP(16, w == 0, 60 + s);
        if (HINT_A && s < HINT_A && w == 1) w_count(G, C_A + 2 * s + crank);
        const uint4 sk = lds128(sb + SM_S + (so >> 4) + crank * 512 + (t128 >> 2) * 16);
        uint32_t kk[11], o[8];
#pragma unroll
        for (int i = 0; i < 11; i++) kk[i] = i < 3 ? lds32(ad[i + 5] + so + (i + 5) * 128) : lds32(ad[(i - 1) & 7] + so + (i + 7) * 128);
#pragma unroll
        for (int i = 0; i < 8; i++) o[i] = lds32(ad[i] + so + KV_V + i * 128);
        const uint32_t w0 = __byte_perm(sk.x, sk.z, 0x5410), w1 = __byte_perm(sk.x, sk.z, 0x7632), w2 = __byte_perm(sk.y, sk.w, 0x5410), w3 = __byte_perm(sk.y, sk.w, 0x7632);
#pragma unroll
        for (int i = 0; i < 8; i++) o[i] = bmul2(bfma2(kk[i + 3], w0, bfma2(kk[i + 2], w1, bfma2(kk[i + 1], w2, bmul2(kk[i], w3)))), o[i]);
#pragma unroll
        for (int i = 0; i < 4; i++) o[2 * i + 1] = bitsel(o[2 * i + 1], par * 0x10001u, mk[i]);
        d[s * 32768] = make_uint4(__byte_perm(o[1], o[0], 0x5410), __byte_perm(o[3], o[2], 0x5410), __byte_perm(o[5], o[4], 0x5410), __byte_perm(o[7], o[6], 0x5410));
        d[s * 32768 + 256] = make_uint4(__byte_perm(o[1], o[0], 0x7632), __byte_perm(o[3], o[2], 0x7632), __byte_perm(o[5], o[4], 0x7632), __byte_perm(o[7], o[6], 0x7632));
        {
          if (HINT_A < 5 && s >= HINT_A && w == 1) w_count(G, C_A + 2 * s + crank);
          w_arrive(BAR(B_KVF + s));
          TSP(1, w == 0, 40 + s);
        }
      }
    }
    if (bid < 100) {
      float d[16];
      zero_acc<16>(d);
      mbar_wait(BAR(B_MT), 0);
#pragma unroll 1
      for (int s = 0; s < 5; s++) {
        const uint64_t da = mkdesc(sb + s * 16384 + (crank ^ 1) * 8192, 0, 1024, 1), db = mkdesc(sb + SM_SILU + s * 128, 16, 128, 0);
        mbar_wait(BAR(B_WM + s), 0);
        TSP(16, w == 0, 80 + s);
        WG_FENCE();
#pragma unroll
        for (int i = 0; i < 4; i++) WSS<8, 1, 0>::mma(d + i * 4, da + i * 128, db + i * 2);
        WG_COMMIT();
      }
      TSP(1, w == 0, 50);
      if (HINT_M && w == 1) w_count(G, C_M + crank);
      WG_WAIT(0);
      if (q == 0) st_relaxed2(G->modp + crank * 3200 + (bid >> 1) * 64 + w * 16 + r * 2, tagw(__float_as_uint((d[0] + d[4]) + (d[8] + d[12])), par), __float_as_uint((d[2] + d[6]) + (d[10] + d[14])));
    }
    if (w == 1 && (!HINT_M || bid >= 100)) w_count(G, C_M + crank);
    w_arrive(BAR(B_WMF));
    TSP(1, w == 0, 51);
    {
      const uint32_t qb = sb + crank * 8192 + (w * 16 + (lane & 15)) * 128 + (((lane >> 4) ^ rr) << 4);
      float red[4] = {0.f, 0.f, 0.f, 0.f};
#pragma unroll
      for (int s = 0; s < 5; s++) {
        uint32_t x[4][4];
        if (s == 0 || s == 3) { mbar_wait(BAR(B_Q + (s & 1)), 0); TSP(17, w == 0, 55 + (s & 1)); }
#pragma unroll
        for (int i = 0; i < 4; i++) ldsm4((qb ^ (i * 32)) + s * 16384, x[i][0], x[i][1], x[i][2], x[i][3]);
#pragma unroll
        for (int h = 0; h < 2; h++) {
          uint32_t su = badd2(x[0][h], x[0][h + 2]), sq = bfma2(x[0][h], x[0][h], bmul2(x[0][h + 2], x[0][h + 2]));
#pragma unroll
          for (int i = 1; i < 4; i++) { su = badd2(su, badd2(x[i][h], x[i][h + 2])); sq = bfma2(x[i][h], x[i][h], bfma2(x[i][h + 2], x[i][h + 2], sq)); }
          red[2 * h] += blo(su) + bhi(su); red[2 * h + 1] += blo(sq) + bhi(sq);
        }
      }
      TSP(1, w == 0, 57);
      bfly<4>(red, lane, 2);
      red[0] += __shfl_xor_sync(0xffffffffu, red[0], 1); red[1] += __shfl_xor_sync(0xffffffffu, red[1], 1);
      const uint32_t to = (q & 1) * peer;
      asm volatile("st.async.weak.shared::cluster.mbarrier::complete_tx::bytes.v2.f32 [%0], {%1, %2}, [%3];"
                   ::"r"(sb + SM_LN1 + ((q >> 1) * 32 + w * 8 + (r & 1) * 4 + (r >> 1)) * 16 + crank * 8 + to), "f"(red[0]), "f"(red[1]), "r"(BAR(B_LN) + to) : "memory");
      TSP(1, w == 0, 60);
    }
  }
  if (STOP_AFTER >= 2) {
    const int a = w & 1, c = w >> 1;
    const uint32_t qa = rr * 128 + ((4 * c ^ rr) << 4) + mi * 2048 + a * 1024, aa = a * 4096 + (32 * c + r) * 64 + ((q ^ (r >> 1)) << 4);
    uint32_t rs[4], ms[4];
    {
      {
        mbar_wait(BAR(B_LN), 0);
        const float4 u = lds128f(sb + SM_LN1 + a * 512 + lane * 16);
        const float mu = (u.x + u.z) * (1.f / 640.f), rq = rsqrtf(fmaxf((u.y + u.w) * (1.f / 640.f) - mu * mu, 0.f) + 1e-5f);
        const uint32_t pk = pack2(rq, -mu * rq);
#pragma unroll
        for (int j = 0; j < 4; j++) {
          const uint32_t e = __shfl_sync(0xffffffffu, pk, 8 * j + q), o = __shfl_sync(0xffffffffu, pk, 8 * j + 4 + q);
          rs[j] = __byte_perm(e, o, 0x5410); ms[j] = __byte_perm(e, o, 0x7632);
        }
        mbar_wait(BAR(B_MT), 1);
        TS1(wg == 2 ? W0(62) : 127);
      }
      uint32_t su[4] = {}, sq[4] = {};
#pragma unroll 1
      for (int s = (wg & 1) * (1 + H2); s < 5; s += (H2 && !s) ? 1 : 2) {
        const uint32_t own = sb + s * 16384 + crank * 8192;
        uint32_t x[4][4];
        mbar_wait(BAR(B_YH + s), 0);
        if (CHAIN && s > H2) bar_sync(1 + wg, 256);
        if (s == 4) TSP(2, w == 0, 99);
#pragma unroll
        for (int i = 0; i < 4; i++) ldsm4t(own + (qa ^ (i * 16)), x[i][0], x[i][1], x[i][2], x[i][3]);
        {
          const uint4 t0 = lds128(sb + SM_MOD + s * 512 + c * 256 + r * 32), t1 = lds128(sb + SM_MOD + s * 512 + c * 256 + r * 32 + 16);
          uint4 y[4];
#pragma unroll
          for (int i = 0; i < 4; i++) y[i] = lds128(sb + s * 16384 + (crank ^ 1) * 8192 + aa + i * 512);
          stage_end();
          TSP(2, w == 0, 1 + s);
#pragma unroll 1
          while (any_stale(stale(stale(stale(y[0].x ^ par, y[1].x, par), y[2].x, par), y[3].x, par))) {
            FX(120);
            int l;
            asm volatile("mov.u32 %0, %%laneid;" : "=r"(l));
#pragma unroll
            for (int i = 0; i < 4; i++) y[i] = ld_relaxed4(G->Y + (s * 128 + crank * 64 + c * 32 + i * 8 + (l >> 2)) * 256 + m * 8 + a * 4 + (l & 3));
          }
          if (CHAIN && s < 4 && s >= H2) bar_arrive(4 - wg, 256);
          w_arrive_peer(BAR(B_RF + s) + peer);
          bar_sync(wg == 1 ? 5 : 1, 128);
          TSP(2, w == 0, 10 + s);
          const uint32_t xf = mbar_test(BAR(B_XF + (s & 1)), ((s >> 1) & 1) ^ 1);
#pragma unroll
          for (int i = 0; i < 4; i++) {
            const uint32_t yv[4] = {y[i].x, y[i].y, y[i].z, y[i].w};
            const uint32_t ca = bdup(i < 2 ? t0.x : t1.x, i & 1), sa = bdup(i < 2 ? t0.y : t1.y, i & 1), cb = bdup(i < 2 ? t0.z : t1.z, i & 1);
#pragma unroll
            for (int j = 0; j < 4; j++) x[i][j] = bfma2(bfma2(bfma2(x[i][j], rs[j], ms[j]), ca, sa), yv[j], x[i][j]);
            y[i] = make_uint4(bmul2(x[i][0], cb), bmul2(x[i][1], cb), bmul2(x[i][2], cb), bmul2(x[i][3], cb));
            sts128(own + aa + i * 512, y[i]);
          }
          const uint32_t rf = mbar_test(BAR(B_RF + s), 0);
          if (a == n >> 1) {
            uint32_t xs = sb + SM_X1 + (s & 1) * 4096 - (mi + a) * 1024;
            asm volatile("" : "+r"(xs));
            if (any_stale(~xf)) mbar_wait(BAR(B_XF + (s & 1)), ((s >> 1) & 1) ^ 1);
#pragma unroll
            for (int i = 0; i < 4; i++) stsm4t(xs + (qa ^ (i * 16)), x[i][0], x[i][1], x[i][2], x[i][3]);
          }
          if (s == 2) TSP(2, w == 0, 97);
          fence_async_s();
          w_arrive(BAR(B_AO + s));
          TSP(2, w == 0, 20 + s);
          if (any_stale(~rf)) mbar_wait(BAR(B_RF + s), 0);
          st_peer4(own + aa + peer, y, BAR(B_AP + s) + peer);
        }
        if (s == 2) TSP(2, w == 0, 98);
#pragma unroll
        for (int j = 0; j < 4; j++) {
          su[j] = badd2(su[j], badd2(badd2(x[0][j], x[1][j]), badd2(x[2][j], x[3][j])));
          sq[j] = badd2(sq[j], bfma2(x[3][j], x[3][j], bfma2(x[2][j], x[2][j], bfma2(x[1][j], x[1][j], bmul2(x[0][j], x[0][j])))));
        }
      }
      const uint32_t lb = sb + SM_LNB + w * 256 + lane * 8;
      uint2 u = make_uint2(0, 0);
      if (wg == 2 - H2) { mbar_wait(BAR(B_LNB), 0); u = lds64(lb); }
      float red[8];
#pragma unroll
      for (int k = 0; k < 4; k++) {
        const uint32_t lo = (k & 1) ? sq[k >> 1] : su[k >> 1], hi = (k & 1) ? sq[2 + (k >> 1)] : su[2 + (k >> 1)];
        const uint32_t mine = (lane & 16) ? hi : lo, other = __shfl_xor_sync(0xffffffffu, (lane & 16) ? lo : hi, 16);
        red[(k >> 1) * 4 + (k & 1)] = blo(mine) + blo(other); red[(k >> 1) * 4 + 2 + (k & 1)] = bhi(mine) + bhi(other);
      }
      bfly<8>(red, lane, 8); bfly<4>(red, lane, 4);
      if (wg == 1 + H2) { sts64(lb, __float_as_uint(red[0]), __float_as_uint(red[1])); w_arrive(BAR(B_LNB)); }
      else {
        const uint32_t la = sb + SM_LN2 + (a * 16 + (q >> 1) * 8 + r) * 64 + (q & 1) * 8 + (crank * 2 + c) * 16;
#pragma unroll
        for (int i = 0; i < 2; i++)
          asm volatile("st.async.weak.shared::cluster.mbarrier::complete_tx::bytes.v2.f32 [%0], {%1, %2}, [%3];" ::"r"(la + i * peer), "f"(red[0] + __uint_as_float(u.x)), "f"(red[1] + __uint_as_float(u.y)), "r"(BAR(B_LN + 1) + i * peer) : "memory");
        TSP(2, w == 0, 30);
      }
    }
  }
  if (wg == 2) {
    if (STOP_AFTER >= 3) {
      const uint32_t to = t128 * 32 + r * 4;
      uint32_t off = 0, ph = 0;
#pragma unroll 1
      for (int i = 0; i < 32; i++) {
        const uint32_t tb = sb + (((uint32_t)(0x9874245000ull >> off) & 255) << 10), vb = BAR(B_VAL) + off;
        mbar_wait(vb - (B_VAL - B_FULL2) * 8, ph);
        if (i < 15) TSP(8, w == 0, 41 + i);
        uint32_t v[7];
#pragma unroll
        for (int k = 0; k < 7; k++) v[k] = lds32(tb + to + k * 4096);
        off += 8;
        if (off == 40) { off = 0; ph ^= 1; }
        if (any_stale(stale(stale(stale(v[0] ^ par, v[1], par), v[2], par), v[3], par) | stale(stale(v[4] ^ par, v[5], par), v[6], par))) {
          FX(121);
#pragma unroll 1
          for (int k = 0; k < 7; k++) refetch(tb + (to & ~31) + k * 4096, G->z2n + (n * 32 + (i & 16) + ((i + ROT * (m >> 3)) & 15)) * IMG + k * 256 + t128 * 2, r * 4, par);
        }
        w_arrive(vb);
        if (i < 15) TSP(8, w == 0, 61 + i);
      }
    }
    goto done;
  }
  asm volatile("setmaxnreg.inc.sync.aligned.u32 192;");
gemm:
  {
    if (STOP_AFTER >= 2) {
      const uint32_t za = sb + SM_PO + (mi >> 1) * 1024 + (16 * w + (mi & 1) * 8 + rr) * 16;
      const bool shifted = !wg ^ (n == 1);
      const int R0 = (m >> 1) * 128 + (m & 1) * 32 + w * 8 + r;
      const uint32_t bs0 = q ? 0 : ldg16(p.bsp + R0), bs1 = q ? 0 : ldg16(p.bsp + R0 + 64);
      float k10, k11, sg0 = 0.f, sg1 = 0.f;
      uint32_t zb[28] = {};
      const uint2* sp = G->st3 + (m * 4 + q) * 64 + w * 8 + r;
      uint2 s3 = make_uint2(0, 0);
      uint32_t* const px = (uint32_t*)(G->z2n + (n * 32 + (m >> 1)) * IMG + (shifted ? 256 : 0) + (m & 1) * 32 + w * 8) + lane;
      uint32_t* const py = px - (shifted ? 7168 : 0);
      auto put = [&](bool on, int h, int j, uint32_t v) { stg32_if(on, (j < 24 ? px : py) + h * 16 * IMG * 4 + j * 256, v); };
      const uint32_t tg = rr == (m & 1) * 4 + w;
      auto ln3 = [&](int h) {
#pragma unroll 1
        while (any_stale(s3.x ^ par)) { FX(119); s3 = ld_relaxed2(sp + h * 32); }
        TSP(2, w == 0, 68 + h);
        const float sg = h ? sg1 : sg0, mu = quad_sum(__uint_as_float(s3.x)) * (1.f / 864.f);
        const float c = rsqrtf(fmaf(4e-5f * sg, sg, fmaxf(quad_sum(__uint_as_float(s3.y)) * (1.f / 864.f) - mu * mu, 0.f)));
        return pack2(c, -mu * c);
      };
      {
        float z[112];
        undef<112>(z);
        float k20, k21;
        {
          bar_sync(wg ? 7 : 10, 256);
#pragma unroll 1
          for (int t = 0; t < 10; t += 2) {
            const int g = wg * 10 + t;
            const uint32_t sx = opaque(sb);
            const uint64_t db = mkdesc(sx + SM_R + (g & 2) * 32768, 8192, 1024, 1), da = mkdesc(sx + t * 8192, 4096, 512, 2);
            const uint32_t fb = BAR(B_FULL1 + (g & 2)), e0 = BAR(t ? B_EMPTY1 + 3 - (g & 2) : B_NIL), x0 = BAR(g == 14 ? B_EMPTY2 : g == 18 ? B_EMPTY2 + 2 : B_NIL), x1 = BAR(g >= 16 ? B_EMPTY2 - 15 + g : B_NIL);
#pragma unroll
            for (int j = 0; j < 2; j++) {
              const uint64_t dx = da + (j ^ crank) * 512;
              mbar_wait2(fb + j * 8, BAR(j ? B_AP : B_AO) + t * 4, (g >> 2) & 1, 0);
              TSP(2, w == 0, 40 + g + j);
              WG_FENCE();
#pragma unroll
              for (int i = 0; i < 4; i++) WSS<32, 1, 1>::mma(z + 96, dx + i * 64, db + j * 2048 + (shifted ? 4 : 1536) + i * 128, i || j || t);
#pragma unroll
              for (int i = 0; i < 4; i++) WSS<192, 1, 1>::mma(z, dx + i * 64, db + j * 2048 + (shifted ? 512 : 0) + i * 128, i || j || t);
              WG_COMMIT();
              WG_WAIT(1);
              if (lane == 0) { mbar_arrive(j ? fb + (B_EMPTY1 - B_FULL1) * 8 : e0); mbar_arrive(j ? x1 : x0); }
            }
          }
          if (!wg && GATE < 0) bar_arrive(7, 256);
          mbar_wait(BAR(B_LN + 1), 0);
          TSP(2, w == 0, 60 + wg);
          const float4 y = lds128f(sb + SM_LN2 + t128 * 16);
          const float m0 = quad_sum(y.x) * (1.f / 640.f), m1 = quad_sum(y.z) * (1.f / 640.f);
          const float v0 = fmaxf(quad_sum(y.y) * (1.f / 640.f) - m0 * m0, 0.f) + 1e-5f, v1 = fmaxf(quad_sum(y.w) * (1.f / 640.f) - m1 * m1, 0.f) + 1e-5f;
          const float h0 = rsqrtf(v0), h1 = rsqrtf(v1);
          sg0 = v0 * h0; sg1 = v1 * h1; k10 = h0 * 0.7978845608028f; k11 = h1 * 0.7978845608028f; k20 = h0 * h0 * h0 * 0.0356774081363f; k21 = h1 * h1 * h1 * 0.0356774081363f;
          const uint32_t ext[4] = {ext_frag(m0, sg0, q), ext_frag(m1, sg1, q), 0u, 0u};
          const uint64_t dv = mkdesc(sb + SM_VT, 0, 128, 0);
          if (wg) mbar_wait(BAR(B_VTF), 0);
          mbar_wait(BAR(B_VT), wg);
          WG_FENCE();
          WRS<32>::mma(z + 96, ext, dv + (shifted ? 0 : 192)); WRS<192>::mma(z, ext, dv + (shifted ? 32 : 0));
          WG_COMMIT();
          if (!wg && GATE == 0) bar_arrive(7, 256);
          WG_WAIT(1);
          if (lane == 0) mbar_arrive(BAR(wg ? B_EMPTY2 + 4 : B_EMPTY1 + 1));
          WG_WAIT(0);
          if (wg) bar_sync(5, 128); else if (lane == 0) mbar_arrive(BAR(B_VTF));
          TSP(2, w == 0, 62 + wg);
        }
        if (!wg) {
          uint32_t z0[28];
#pragma unroll
          for (int h = 0; h < 2; h++) {
            float s0, q0, s1, q1, s2, q2;
#pragma unroll
            for (int j = 0; j < 28; j++) {
              if (j == LOAD_AT && h) s3 = ld_relaxed2(sp);
              if (j == PUB_AT && h) {
                const uint32_t cp = ln3(0);
#pragma unroll
                for (int i = 0; i < 28; i++) put(true, 0, i, bitsel(baffine(z0[i], cp), par, tg));
                TSP(2, w == 0, 70);
              }
              const float a = gelu2(z[4 * j + 2 * h], h ? k11 : k10, h ? k21 : k20), b = gelu2(z[4 * j + 2 * h + 1], h ? k11 : k10, h ? k21 : k20);
              (h ? zb : z0)[j] = pack2(a, b);
              if (j == 0) { s0 = a; s1 = b; q0 = a * a; q1 = b * b; }
              else { s0 += a; s1 += b; q0 = fmaf(a, a, q0); q1 = fmaf(b, b, q1); }
              if (j == 23) { s2 = s0 + s1; q2 = q0 + q1; }
              if (h && j % PSTEP == PSTEP - 1) stage_end();
            }
            s0 = quad_sum(n == 3 ? s2 : s0 + s1); q0 = quad_sum(n == 3 ? q2 : q0 + q1);
            if (q == n) st_relaxed2((uint2*)sp + h * 32, tagw(__float_as_uint(s0), par), __float_as_uint(q0));
            if (!h && w == 1) w_count_timed(G, C_G + crank);
            TSP(2, w == 0, 64 + h);
            stage_end();
          }
          sleep_for(WAIT1);
          s3 = ld_relaxed2(sp + 32);
          const uint32_t cp = ln3(1);
#pragma unroll
          for (int j = 0; j < 28; j++) { zb[j] = bitsel(baffine(zb[j], cp), par, tg); if (STOP_AFTER < 3) put(true, 1, j, zb[j]); }
          TSP(2, w == 0, 71);
          if (STOP_AFTER < 3) w_arrive(BAR(B_PUB));
        } else if (STOP_AFTER >= 3) {
          uint32_t zx = za + (shifted ? 4096 : 0), zy = za - (shifted ? 24576 : 0);
          asm volatile("" : "+r"(zx), "+r"(zy));
#pragma unroll
          for (int j = 0; j < 28; j += 2) stsm4((j < 24 ? zx : zy) + j * 1024, pack2(z[4 * j], z[4 * j + 1]), pack2(z[4 * j + 2], z[4 * j + 3]), pack2(z[4 * j + 4], z[4 * j + 5]), pack2(z[4 * j + 6], z[4 * j + 7]));
          __syncwarp();
          TSP(2, w == 0, 66);
#pragma unroll 1
          for (int j = 0; j < 14; j++) {
            const float cs = n == 3 && j < 2 ? 0.f : 0.5f / 0.7978845608028f, c0 = k10 * cs, c1 = k11 * cs;
            uint32_t v[4];
            ldsm4(za + j * 2048, v[0], v[1], v[2], v[3]);
#pragma unroll
            for (int i = 0; i < 4; i++) v[i] = pack2(gelu2(blo(v[i]), (i & 1) ? k11 : k10, (i & 1) ? k21 : k20) * ((i & 1) ? c1 : c0), gelu2(bhi(v[i]), (i & 1) ? k11 : k10, (i & 1) ? k21 : k20) * ((i & 1) ? c1 : c0));
            stsm4(za + j * 2048, v[0], v[1], v[2], v[3]);
          }
          w_arrive(BAR(B_Z1S));
        }
        TSP(2, w == 0, 72 + wg);
      }
      if (STOP_AFTER >= 3) {
        if (!wg) {
          float g[112];
          {
            const uint32_t bias[4] = {bs0, bs1, 0u, 0u};
            WG_FENCE();
            wrs96_first(g + 64, bias, mkdesc(sb + SM_ONE, 0, 0, 0)); wrs128_first(g, bias, mkdesc(sb + SM_ONE, 0, 0, 0));
            WG_COMMIT();
          }
#pragma unroll 1
          for (int rnd = 0;; rnd++) {
            const uint32_t sx = opaque(sb);
            const uint64_t dA2 = mkdesc(sx, 16, 1024, 1), dB2 = mkdesc(sx, 128, 1024, 0);
            const uint32_t fb = BAR(B_VAL), e0 = BAR(rnd ? B_EMPTY2 + 4 : B_NIL);
#pragma unroll
            for (int st = 0; st < 5; st++) {
              const uint64_t da = dA2 + (placeA(st) >> 4), db = dB2 + (placeB(st) >> 4);
              if (rnd < 3) TSP(8, w == 0, rnd * 5 + st + 1);
              mbar_wait(fb + st * 8, rnd & 1);
              if (rnd < 3) TSP(8, w == 0, rnd * 5 + st + 21);
              if (st == 0 || rnd == 0) TSP(4, w == 0, st ? 10 + st : 1 + rnd);
              WG_FENCE();
#pragma unroll
              for (int j = 0; j < 4; j++) { WSS<96, 0, 1>::mma(g + 64, da + j * 2, db + j * 16 + 1024); put(rnd == 0, 1, 6 * st + j, zb[6 * st + j]); }
#pragma unroll
              for (int j = 0; j < 4; j++) { WSS<128, 0, 1>::mma(g, da + j * 2, db + j * 16); if (j < 2 && st < 4) put(rnd == 0, 1, 6 * st + 4 + j, zb[6 * st + 4 + j]); }
              WG_COMMIT();
              WG_WAIT(1);
              if (lane == 0) mbar_arrive(st ? BAR(B_EMPTY2 + st - 1) : e0);
              if (st == 4 && lane == 0) mbar_arrive(BAR(rnd ? B_NIL : B_PUB));
              if (st == 1 && rnd == 6) goto g2_done;
            }
          }
        g2_done:
          w_arrive_peer(BAR(B_PFREE) + peer);
          if (STOP_AFTER >= 4) bar_arrive(13, 256);
          mbar_wait(BAR(B_Z1S), 0);
          uint32_t z1[56];
#pragma unroll
          for (int j = 0; j < 28; j += 2) ldsm4(za + j * 1024, z1[2 * j], z1[2 * j + 1], z1[2 * j + 2], z1[2 * j + 3]);
          WG_WAIT(0);
          if (lane == 0) mbar_arrive(BAR(B_EMPTY2 + 1));
          TSP(4, w == 0, 20);
#pragma unroll
          for (int j = 0; j < 28; j += 2) {
#pragma unroll
            for (int i = 2 * j; i < 2 * j + 4; i++) z1[i] = bmul2(z1[i], pack2(g[2 * i], g[2 * i + 1]));
            stsm4(za + j * 1024, z1[2 * j], z1[2 * j + 1], z1[2 * j + 2], z1[2 * j + 3]);
            if ((j == 12 && !PONE) || j == 26) { fence_async_s(); w_arrive(BAR(B_PST + (j >> 4))); TSP(4, w == 0, 21 + (j >> 4)); stage_end(); }
          }
        }
      }
      if (STOP_AFTER >= 4) {
        float o[64];
        undef<64>(o);
        mbar_wait(BAR(B_GB), 0);
#pragma unroll 1
        for (int it = 0; it <= wg; it++) {
          const int box = it ? 4 : 2 - 2 * wg;
          uint4 gb[4];
#pragma unroll
          for (int i = 0; i < 4; i++) gb[i] = lds128(sb + SM_GB + box * 128 + i * 64 + q * 16);
#pragma unroll 1
          for (int t = 0; t < 2; t++) {
            const uint32_t sx = opaque(sb);
            const uint64_t da = mkdesc(sx + (t ? 0 : SM_PO), 1024, 128, 0);
            if (!(it & t)) bar_sync(12 + wg, 256);
            if (!it) {
              const uint32_t f0 = BAR(B_FULL2 + 4 - 2 * wg), f1 = BAR(B_FULL2 + 1 + 2 * wg), pb = BAR(t ? B_PP : B_PST);
#pragma unroll
              for (int j = 0; j < 2; j++) {
                const uint64_t db = mkdesc(sx + (wg ? placeB(2 + j) : placeB(4 - 3 * j)), 14336, 1024, 1);
                mbar_wait2(j ? f1 : f0, pb + (j || (PONE && !t)) * 8, t ^ (j & ~wg), 0);
                TSP(4, w == 0, 32 - 2 * wg + 4 * t + j);
                WG_FENCE();
#pragma unroll
                for (int i = 0; i < 7; i++) WSS<128, 0, 1>::mma(o, da + j * 896 + i * 128, db + i * 128, i || j || t);
                WG_COMMIT();
              }
              bar_arrive(13 - wg, 256);
              WG_WAIT(1);
              if (lane == 0) mbar_arrive(f0 + (B_EMPTY2 - B_FULL2) * 8);
              WG_WAIT(0);
              if (lane == 0) mbar_arrive(f1 + (B_EMPTY2 - B_FULL2) * 8);
            } else {
              const uint64_t db = mkdesc(sx + (t ? placeB(3) : placeB(2)), 0, 1024, 1);
              mbar_wait(BAR(B_FULL2 + 2 + t), 0);
              TSP(4, w == 0, 38 + t);
              WG_FENCE();
#pragma unroll
              for (int i = 0; i < 14; i++) WSS<64, 0, 1>::mma(o, da + i * 128, db + i * 128, i || t);
              WG_COMMIT();
            }
          }
          if (it == wg) w_arrive(BAR(B_DONE + wg));
          WG_WAIT(0);
          TSP(4, w == 0, 40 + it + 2 * !wg);
#pragma unroll
          for (int b = 0; b < 2; b++) {
            const uint32_t ob = sb + placeA(box + b) + w * 2048, oa = ob + (lane & 15) * 128 + (((mi >> 1) ^ rr) << 4);
#pragma unroll
            for (int i = 0; i < 4; i++) {
              const float* a = o + b * 32 + i * 8;
              const uint4 gq = gb[2 * b + (i >> 1)];
              const uint32_t g0 = (i & 1) ? gq.z : gq.x, g1 = (i & 1) ? gq.w : gq.y;
              stsm4(oa ^ (i * 32), bmul2(pack2(a[0], a[1]), g0), bmul2(pack2(a[2], a[3]), g0), bmul2(pack2(a[4], a[5]), g1), bmul2(pack2(a[6], a[7]), g1));
            }
            fence_async_s();
            __syncwarp();
            tma_rows_add(&tm.out, (box + b) * 128 + crank * 64, m & ~1, (m & 1) * 4 + w, ob);
            TSP(4, w == 0, 50 + box + b);
            if (it) break;
          }
        }
        bulk_commit();
        bulk_wait_read0();
        TSP(4, w == 0, 56 + wg);
        return;
      }
    }
  }
done:
  w_arrive(BAR(B_DONE + wg));
}

typedef CUresult (*EncodeFn)(CUtensorMap*, CUtensorMapDataType, cuuint32_t, void*, const cuuint64_t*, const cuuint64_t*, const cuuint32_t*, const cuuint32_t*,
                             CUtensorMapInterleave, CUtensorMapSwizzle, CUtensorMapL2promotion, CUtensorMapFloatOOBfill);
struct Dim { uint64_t size, stride; uint32_t box; };

CUtensorMap make_map(EncodeFn enc, const void* ptr, uint64_t cols, Dim a, Dim b = {0, 0, 0}, Dim c = {0, 0, 0}, Dim d = {0, 0, 0}, uint32_t width = 64) {
  CUtensorMap m;
  cuuint64_t gd[5] = {cols, a.size, b.size, c.size, d.size}, gs[4] = {a.stride, b.stride, c.stride, d.stride};
  cuuint32_t bd[5] = {width, a.box, b.box, c.box, d.box}, es[5] = {1, 1, 1, 1, 1};
  enc(&m, CU_TENSOR_MAP_DATA_TYPE_BFLOAT16, d.size ? 5 : c.size ? 4 : b.size ? 3 : 2, const_cast<void*>(ptr), gd, gs, bd, es, CU_TENSOR_MAP_INTERLEAVE_NONE,
      width == 64 ? CU_TENSOR_MAP_SWIZZLE_128B : width == 32 ? CU_TENSOR_MAP_SWIZZLE_64B : CU_TENSOR_MAP_SWIZZLE_NONE, CU_TENSOR_MAP_L2_PROMOTION_L2_128B, CU_TENSOR_MAP_FLOAT_OOB_FILL_NONE);
  return m;
}

}

extern "C" void kernel_launch(void* const* d_in, const int* in_sizes, int n_in, void* d_out, int out_size) {
  (void)in_sizes; (void)n_in; (void)out_size;
  void* fn = nullptr;
  cudaDriverEntryPointQueryResult qr;
  cudaGetDriverEntryPoint("cuTensorMapEncodeTiled", &fn, cudaEnableDefault, &qr);
  EncodeFn enc = (EncodeFn)fn;
  Params p;
  p.k = (const __nv_bfloat16*)d_in[1]; p.v = (const __nv_bfloat16*)d_in[2];
  p.shiftk = (const __nv_bfloat16*)d_in[3]; p.ssmk = (const __nv_bfloat16*)d_in[4]; p.ssmD = (const __nv_bfloat16*)d_in[5];
  p.bsp = (const __nv_bfloat16*)d_in[9]; p.c = (const __nv_bfloat16*)d_in[11]; p.wout = (const __nv_bfloat16*)d_in[10];
  p.wsp = (const __nv_bfloat16*)d_in[8];
  void* scr = nullptr;
  cudaGetSymbolAddress(&scr, g_scr);
  p.g = (Scratch*)scr;
  int dev = 0, nsm = 0;
  cudaGetDevice(&dev);
  cudaDeviceGetAttribute(&nsm, cudaDevAttrMultiProcessorCount, dev);
  p.by_sm = nsm == 132;
  for (int t = 0; t < 64; t++) {
    const int grp = t < 32 ? t & 7 : t < 60 ? (t - 32) % 7 + 1 : 0, i = t < 32 ? t >> 3 : t < 60 ? 4 + (t - 32) / 7 : t - 56;
    p.tile[t] = ((grp >> 1) * 8 + i) * 2 + (grp & 1);
  }
  const Dim one = {1, 16, 1};
  Maps tm;
  tm.k = make_map(enc, d_in[1], 640, {8, 1280, 10}, {256, 10240, 5}, one, one);
  tm.v = make_map(enc, d_in[2], 640, {8, 1280, 10}, {256, 10240, 4}, one, one);
  tm.f = make_map(enc, d_in[4], 256, {8, 512, 8}, {640, 4096, 1}, one, one, 256);
  tm.wm = make_map(enc, d_in[12], 3840, {640, 7680, 64}, one, one, one);
  tm.q = make_map(enc, d_in[0], 640, {2, 1280, 2}, {32, 81920, 2}, {8, 10240, 4}, {4, 2560, 4});
  tm.y = make_map(enc, p.g->Y, 32, {640, 4096, 64}, {64, 64, 2}, {0, 0, 0}, {0, 0, 0}, 32);
  tm.wm2 = make_map(enc, d_in[12], 64, {640, 7680, 64}, {60, 128, 2});
  tm.w2 = make_map(enc, d_in[7], 64, {640, 3456, 64}, {27, 128, 2});
  tm.wsp = make_map(enc, d_in[8], 2048, {8, 4096, 8}, {32, 262144, 2}, {8, 32768, 4});
  tm.x1 = make_map(enc, d_out, 640, {2, 1280, 2}, {32, 81920, 2}, {8, 10240, 2}, {4, 2560, 4});
  tm.out = make_map(enc, d_out, 640, {8, 1280, 8}, {32, 81920, 2}, {8, 10240, 1});
  tm.wo = make_map(enc, d_in[10], 640, {864, 1280, 112});
  cudaFuncSetAttribute(fused_kernel, cudaFuncAttributeMaxDynamicSharedMemorySize, SM_TOTAL);
  cudaLaunchConfig_t cfg = {};
  cfg.gridDim = dim3(132); cfg.blockDim = dim3(512); cfg.dynamicSmemBytes = SM_TOTAL; cfg.stream = cudaStreamPerThread;
  cudaLaunchAttribute at[1];
  at[0].id = cudaLaunchAttributeCooperative; at[0].val.cooperative = 1;
  cfg.attrs = at; cfg.numAttrs = 1;
  cudaLaunchKernelEx(&cfg, fused_kernel, p, tm);
}
```

```cpp
#include <cuda_runtime.h>
#include <cuda.h>
#include <cuda_bf16.h>
#include <stdint.h>
#include <string.h>
#include <stddef.h>

#define SEQ0 0x1202211101201000ull
#define SEQ1 0x3130231404221303ull
#define SEQ2 0x4342414024343332ull
#define SEQ3 0x44ull
#define WPOS 14
#define T_2 1050
#define T_AB 1800
#define PACE_D 370
#define PACE_F 355
#define PACE_Q 355
#define PACE_W 555
#define T_WIN 13000
#define T_SPARE 11000
#define LOAD_AT 8
#define PUB_AT 16
#define WAIT1 600
#define GATE 1
#define HINT_A 2
#define CHAIN 1
#define PSTEP 4
#define POLL0 300
#define DELAY0 1700
#define POLL1 600
#define NAPA 700
#define NAPS 1
#define NAPM 500
#define HINT_M 1
#define H2 0
#define ZINIT 0
#define MAP44 0
#define MCAST 0
#define BOXX 2
#define XGAP 150
#define ROT 0
#define PONE 1
#define PGATE 3
#define STOP_AFTER 99

namespace {

template<int N> struct WRS;
template<int N, int TA, int TB> struct WSS;
template<> struct WRS<16> { static __device__ __forceinline__ void mma(float* d, const uint32_t* a, uint64_t db) {
  asm volatile("wgmma.mma_async.sync.aligned.m64n16k16.f32.bf16.bf16 {%0,%1,%2,%3,%4,%5,%6,%7}, {%8,%9,%10,%11}, %12, 1, 1, 1, 0;"
    : "+f"(d[0]),"+f"(d[1]),"+f"(d[2]),"+f"(d[3]),"+f"(d[4]),"+f"(d[5]),"+f"(d[6]),"+f"(d[7])
    : "r"(a[0]), "r"(a[1]), "r"(a[2]), "r"(a[3]), "l"(db)); } };
template<> struct WRS<32> { static __device__ __forceinline__ void mma(float* d, const uint32_t* a, uint64_t db) {
  asm volatile("wgmma.mma_async.sync.aligned.m64n32k16.f32.bf16.bf16 {%0,%1,%2,%3,%4,%5,%6,%7,%8,%9,%10,%11,%12,%13,%14,%15}, {%16,%17,%18,%19}, %20, 1, 1, 1, 0;"
    : "+f"(d[0]),"+f"(d[1]),"+f"(d[2]),"+f"(d[3]),"+f"(d[4]),"+f"(d[5]),"+f"(d[6]),"+f"(d[7]),"+f"(d[8]),"+f"(d[9]),"+f"(d[10]),"+f"(d[11]),"+f"(d[12]),"+f"(d[13]),"+f"(d[14]),"+f"(d[15])
    : "r"(a[0]), "r"(a[1]), "r"(a[2]), "r"(a[3]), "l"(db)); } };
template<> struct WRS<48> { static __device__ __forceinline__ void mma(float* d, const uint32_t* a, uint64_t db) {
  asm volatile("wgmma.mma_async.sync.aligned.m64n48k16.f32.bf16.bf16 {%0,%1,%2,%3,%4,%5,%6,%7,%8,%9,%10,%11,%12,%13,%14,%15,%16,%17,%18,%19,%20,%21,%22,%23}, {%24,%25,%26,%27}, %28, 1, 1, 1, 0;"
    : "+f"(d[0]),"+f"(d[1]),"+f"(d[2]),"+f"(d[3]),"+f"(d[4]),"+f"(d[5]),"+f"(d[6]),"+f"(d[7]),"+f"(d[8]),"+f"(d[9]),"+f"(d[10]),"+f"(d[11]),"+f"(d[12]),"+f"(d[13]),"+f"(d[14]),"+f"(d[15]),"+f"(d[16]),"+f"(d[17]),"+f"(d[18]),"+f"(d[19]),"+f"(d[20]),"+f"(d[21]),"+f"(d[22]),"+f"(d[23])
    : "r"(a[0]), "r"(a[1]), "r"(a[2]), "r"(a[3]), "l"(db)); } };
template<> struct WRS<64> { static __device__ __forceinline__ void mma(float* d, const uint32_t* a, uint64_t db) {
  asm volatile("wgmma.mma_async.sync.aligned.m64n64k16.f32.bf16.bf16 {%0,%1,%2,%3,%4,%5,%6,%7,%8,%9,%10,%11,%12,%13,%14,%15,%16,%17,%18,%19,%20,%21,%22,%23,%24,%25,%26,%27,%28,%29,%30,%31}, {%32,%33,%34,%35}, %36, 1, 1, 1, 0;"
    : "+f"(d[0]),"+f"(d[1]),"+f"(d[2]),"+f"(d[3]),"+f"(d[4]),"+f"(d[5]),"+f"(d[6]),"+f"(d[7]),"+f"(d[8]),"+f"(d[9]),"+f"(d[10]),"+f"(d[11]),"+f"(d[12]),"+f"(d[13]),"+f"(d[14]),"+f"(d[15]),"+f"(d[16]),"+f"(d[17]),"+f"(d[18]),"+f"(d[19]),"+f"(d[20]),"+f"(d[21]),"+f"(d[22]),"+f"(d[23]),"+f"(d[24]),"+f"(d[25]),"+f"(d[26]),"+f"(d[27]),"+f"(d[28]),"+f"(d[29]),"+f"(d[30]),"+f"(d[31])
    : "r"(a[0]), "r"(a[1]), "r"(a[2]), "r"(a[3]), "l"(db)); } };
template<> struct WRS<80> { static __device__ __forceinline__ void mma(float* d, const uint32_t* a, uint64_t db) {
  asm volatile("wgmma.mma_async.sync.aligned.m64n80k16.f32.bf16.bf16 {%0,%1,%2,%3,%4,%5,%6,%7,%8,%9,%10,%11,%12,%13,%14,%15,%16,%17,%18,%19,%20,%21,%22,%23,%24,%25,%26,%27,%28,%29,%30,%31,%32,%33,%34,%35,%36,%37,%38,%39}, {%40,%41,%42,%43}, %44, 1, 1, 1, 0;"
    : "+f"(d[0]),"+f"(d[1]),"+f"(d[2]),"+f"(d[3]),"+f"(d[4]),"+f"(d[5]),"+f"(d[6]),"+f"(d[7]),"+f"(d[8]),"+f"(d[9]),"+f"(d[10]),"+f"(d[11]),"+f"(d[12]),"+f"(d[13]),"+f"(d[14]),"+f"(d[15]),"+f"(d[16]),"+f"(d[17]),"+f"(d[18]),"+f"(d[19]),"+f"(d[20]),"+f"(d[21]),"+f"(d[22]),"+f"(d[23]),"+f"(d[24]),"+f"(d[25]),"+f"(d[26]),"+f"(d[27]),"+f"(d[28]),"+f"(d[29]),"+f"(d[30]),"+f"(d[31]),"+f"(d[32]),"+f"(d[33]),"+f"(d[34]),"+f"(d[35]),"+f"(d[36]),"+f"(d[37]),"+f"(d[38]),"+f"(d[39])
    : "r"(a[0]), "r"(a[1]), "r"(a[2]), "r"(a[3]), "l"(db)); } };
template<> struct WRS<96> { static __device__ __forceinline__ void mma(float* d, const uint32_t* a, uint64_t db) {
  asm volatile("wgmma.mma_async.sync.aligned.m64n96k16.f32.bf16.bf16 {%0,%1,%2,%3,%4,%5,%6,%7,%8,%9,%10,%11,%12,%13,%14,%15,%16,%17,%18,%19,%20,%21,%22,%23,%24,%25,%26,%27,%28,%29,%30,%31,%32,%33,%34,%35,%36,%37,%38,%39,%40,%41,%42,%43,%44,%45,%46,%47}, {%48,%49,%50,%51}, %52, 1, 1, 1, 0;"
    : "+f"(d[0]),"+f"(d[1]),"+f"(d[2]),"+f"(d[3]),"+f"(d[4]),"+f"(d[5]),"+f"(d[6]),"+f"(d[7]),"+f"(d[8]),"+f"(d[9]),"+f"(d[10]),"+f"(d[11]),"+f"(d[12]),"+f"(d[13]),"+f"(d[14]),"+f"(d[15]),"+f"(d[16]),"+f"(d[17]),"+f"(d[18]),"+f"(d[19]),"+f"(d[20]),"+f"(d[21]),"+f"(d[22]),"+f"(d[23]),"+f"(d[24]),"+f"(d[25]),"+f"(d[26]),"+f"(d[27]),"+f"(d[28]),"+f"(d[29]),"+f"(d[30]),"+f"(d[31]),"+f"(d[32]),"+f"(d[33]),"+f"(d[34]),"+f"(d[35]),"+f"(d[36]),"+f"(d[37]),"+f"(d[38]),"+f"(d[39]),"+f"(d[40]),"+f"(d[41]),"+f"(d[42]),"+f"(d[43]),"+f"(d[44]),"+f"(d[45]),"+f"(d[46]),"+f"(d[47])
    : "r"(a[0]), "r"(a[1]), "r"(a[2]), "r"(a[3]), "l"(db)); } };
template<> struct WRS<112> { static __device__ __forceinline__ void mma(float* d, const uint32_t* a, uint64_t db) {
  asm volatile("wgmma.mma_async.sync.aligned.m64n112k16.f32.bf16.bf16 {%0,%1,%2,%3,%4,%5,%6,%7,%8,%9,%10,%11,%12,%13,%14,%15,%16,%17,%18,%19,%20,%21,%22,%23,%24,%25,%26,%27,%28,%29,%30,%31,%32,%33,%34,%35,%36,%37,%38,%39,%40,%41,%42,%43,%44,%45,%46,%47,%48,%49,%50,%51,%52,%53,%54,%55}, {%56,%57,%58,%59}, %60, 1, 1, 1, 0;"
    : "+f"(d[0]),"+f"(d[1]),"+f"(d[2]),"+f"(d[3]),"+f"(d[4]),"+f"(d[5]),"+f"(d[6]),"+f"(d[7]),"+f"(d[8]),"+f"(d[9]),"+f"(d[10]),"+f"(d[11]),"+f"(d[12]),"+f"(d[13]),"+f"(d[14]),"+f"(d[15]),"+f"(d[16]),"+f"(d[17]),"+f"(d[18]),"+f"(d[19]),"+f"(d[20]),"+f"(d[21]),"+f"(d[22]),"+f"(d[23]),"+f"(d[24]),"+f"(d[25]),"+f"(d[26]),"+f"(d[27]),"+f"(d[28]),"+f"(d[29]),"+f"(d[30]),"+f"(d[31]),"+f"(d[32]),"+f"(d[33]),"+f"(d[34]),"+f"(d[35]),"+f"(d[36]),"+f"(d[37]),"+f"(d[38]),"+f"(d[39]),"+f"(d[40]),"+f"(d[41]),"+f"(d[42]),"+f"(d[43]),"+f"(d[44]),"+f"(d[45]),"+f"(d[46]),"+f"(d[47]),"+f"(d[48]),"+f"(d[49]),"+f"(d[50]),"+f"(d[51]),"+f"(d[52]),"+f"(d[53]),"+f"(d[54]),"+f"(d[55])
    : "r"(a[0]), "r"(a[1]), "r"(a[2]), "r"(a[3]), "l"(db)); } };
template<> struct WRS<128> { static __device__ __forceinline__ void mma(float* d, const uint32_t* a, uint64_t db) {
  asm volatile("wgmma.mma_async.sync.aligned.m64n128k16.f32.bf16.bf16 {%0,%1,%2,%3,%4,%5,%6,%7,%8,%9,%10,%11,%12,%13,%14,%15,%16,%17,%18,%19,%20,%21,%22,%23,%24,%25,%26,%27,%28,%29,%30,%31,%32,%33,%34,%35,%36,%37,%38,%39,%40,%41,%42,%43,%44,%45,%46,%47,%48,%49,%50,%51,%52,%53,%54,%55,%56,%57,%58,%59,%60,%61,%62,%63}, {%64,%65,%66,%67}, %68, 1, 1, 1, 0;"
    : "+f"(d[0]),"+f"(d[1]),"+f"(d[2]),"+f"(d[3]),"+f"(d[4]),"+f"(d[5]),"+f"(d[6]),"+f"(d[7]),"+f"(d[8]),"+f"(d[9]),"+f"(d[10]),"+f"(d[11]),"+f"(d[12]),"+f"(d[13]),"+f"(d[14]),"+f"(d[15]),"+f"(d[16]),"+f"(d[17]),"+f"(d[18]),"+f"(d[19]),"+f"(d[20]),"+f"(d[21]),"+f"(d[22]),"+f"(d[23]),"+f"(d[24]),"+f"(d[25]),"+f"(d[26]),"+f"(d[27]),"+f"(d[28]),"+f"(d[29]),"+f"(d[30]),"+f"(d[31]),"+f"(d[32]),"+f"(d[33]),"+f"(d[34]),"+f"(d[35]),"+f"(d[36]),"+f"(d[37]),"+f"(d[38]),"+f"(d[39]),"+f"(d[40]),"+f"(d[41]),"+f"(d[42]),"+f"(d[43]),"+f"(d[44]),"+f"(d[45]),"+f"(d[46]),"+f"(d[47]),"+f"(d[48]),"+f"(d[49]),"+f"(d[50]),"+f"(d[51]),"+f"(d[52]),"+f"(d[53]),"+f"(d[54]),"+f"(d[55]),"+f"(d[56]),"+f"(d[57]),"+f"(d[58]),"+f"(d[59]),"+f"(d[60]),"+f"(d[61]),"+f"(d[62]),"+f"(d[63])
    : "r"(a[0]), "r"(a[1]), "r"(a[2]), "r"(a[3]), "l"(db)); } };
template<> struct WRS<192> { static __device__ __forceinline__ void mma(float* d, const uint32_t* a, uint64_t db) {
  asm volatile("wgmma.mma_async.sync.aligned.m64n192k16.f32.bf16.bf16 {%0,%1,%2,%3,%4,%5,%6,%7,%8,%9,%10,%11,%12,%13,%14,%15,%16,%17,%18,%19,%20,%21,%22,%23,%24,%25,%26,%27,%28,%29,%30,%31,%32,%33,%34,%35,%36,%37,%38,%39,%40,%41,%42,%43,%44,%45,%46,%47,%48,%49,%50,%51,%52,%53,%54,%55,%56,%57,%58,%59,%60,%61,%62,%63,%64,%65,%66,%67,%68,%69,%70,%71,%72,%73,%74,%75,%76,%77,%78,%79,%80,%81,%82,%83,%84,%85,%86,%87,%88,%89,%90,%91,%92,%93,%94,%95}, {%96,%97,%98,%99}, %100, 1, 1, 1, 0;"
    : "+f"(d[0]),"+f"(d[1]),"+f"(d[2]),"+f"(d[3]),"+f"(d[4]),"+f"(d[5]),"+f"(d[6]),"+f"(d[7]),"+f"(d[8]),"+f"(d[9]),"+f"(d[10]),"+f"(d[11]),"+f"(d[12]),"+f"(d[13]),"+f"(d[14]),"+f"(d[15]),"+f"(d[16]),"+f"(d[17]),"+f"(d[18]),"+f"(d[19]),"+f"(d[20]),"+f"(d[21]),"+f"(d[22]),"+f"(d[23]),"+f"(d[24]),"+f"(d[25]),"+f"(d[26]),"+f"(d[27]),"+f"(d[28]),"+f"(d[29]),"+f"(d[30]),"+f"(d[31]),"+f"(d[32]),"+f"(d[33]),"+f"(d[34]),"+f"(d[35]),"+f"(d[36]),"+f"(d[37]),"+f"(d[38]),"+f"(d[39]),"+f"(d[40]),"+f"(d[41]),"+f"(d[42]),"+f"(d[43]),"+f"(d[44]),"+f"(d[45]),"+f"(d[46]),"+f"(d[47]),"+f"(d[48]),"+f"(d[49]),"+f"(d[50]),"+f"(d[51]),"+f"(d[52]),"+f"(d[53]),"+f"(d[54]),"+f"(d[55]),"+f"(d[56]),"+f"(d[57]),"+f"(d[58]),"+f"(d[59]),"+f"(d[60]),"+f"(d[61]),"+f"(d[62]),"+f"(d[63]),"+f"(d[64]),"+f"(d[65]),"+f"(d[66]),"+f"(d[67]),"+f"(d[68]),"+f"(d[69]),"+f"(d[70]),"+f"(d[71]),"+f"(d[72]),"+f"(d[73]),"+f"(d[74]),"+f"(d[75]),"+f"(d[76]),"+f"(d[77]),"+f"(d[78]),"+f"(d[79]),"+f"(d[80]),"+f"(d[81]),"+f"(d[82]),"+f"(d[83]),"+f"(d[84]),"+f"(d[85]),"+f"(d[86]),"+f"(d[87]),"+f"(d[88]),"+f"(d[89]),"+f"(d[90]),"+f"(d[91]),"+f"(d[92]),"+f"(d[93]),"+f"(d[94]),"+f"(d[95])
    : "r"(a[0]), "r"(a[1]), "r"(a[2]), "r"(a[3]), "l"(db)); } };
template<> struct WSS<192,1,1> { static __device__ __forceinline__ void mma(float* d, uint64_t da, uint64_t db, int acc = 1) {
  asm volatile("{\n.reg .pred p;\nsetp.ne.b32 p, %98, 0;\nwgmma.mma_async.sync.aligned.m64n192k16.f32.bf16.bf16 {%0,%1,%2,%3,%4,%5,%6,%7,%8,%9,%10,%11,%12,%13,%14,%15,%16,%17,%18,%19,%20,%21,%22,%23,%24,%25,%26,%27,%28,%29,%30,%31,%32,%33,%34,%35,%36,%37,%38,%39,%40,%41,%42,%43,%44,%45,%46,%47,%48,%49,%50,%51,%52,%53,%54,%55,%56,%57,%58,%59,%60,%61,%62,%63,%64,%65,%66,%67,%68,%69,%70,%71,%72,%73,%74,%75,%76,%77,%78,%79,%80,%81,%82,%83,%84,%85,%86,%87,%88,%89,%90,%91,%92,%93,%94,%95}, %96, %97, p, 1, 1, 1, 1;\n}"
    : "+f"(d[0]),"+f"(d[1]),"+f"(d[2]),"+f"(d[3]),"+f"(d[4]),"+f"(d[5]),"+f"(d[6]),"+f"(d[7]),"+f"(d[8]),"+f"(d[9]),"+f"(d[10]),"+f"(d[11]),"+f"(d[12]),"+f"(d[13]),"+f"(d[14]),"+f"(d[15]),"+f"(d[16]),"+f"(d[17]),"+f"(d[18]),"+f"(d[19]),"+f"(d[20]),"+f"(d[21]),"+f"(d[22]),"+f"(d[23]),"+f"(d[24]),"+f"(d[25]),"+f"(d[26]),"+f"(d[27]),"+f"(d[28]),"+f"(d[29]),"+f"(d[30]),"+f"(d[31]),"+f"(d[32]),"+f"(d[33]),"+f"(d[34]),"+f"(d[35]),"+f"(d[36]),"+f"(d[37]),"+f"(d[38]),"+f"(d[39]),"+f"(d[40]),"+f"(d[41]),"+f"(d[42]),"+f"(d[43]),"+f"(d[44]),"+f"(d[45]),"+f"(d[46]),"+f"(d[47]),"+f"(d[48]),"+f"(d[49]),"+f"(d[50]),"+f"(d[51]),"+f"(d[52]),"+f"(d[53]),"+f"(d[54]),"+f"(d[55]),"+f"(d[56]),"+f"(d[57]),"+f"(d[58]),"+f"(d[59]),"+f"(d[60]),"+f"(d[61]),"+f"(d[62]),"+f"(d[63]),"+f"(d[64]),"+f"(d[65]),"+f"(d[66]),"+f"(d[67]),"+f"(d[68]),"+f"(d[69]),"+f"(d[70]),"+f"(d[71]),"+f"(d[72]),"+f"(d[73]),"+f"(d[74]),"+f"(d[75]),"+f"(d[76]),"+f"(d[77]),"+f"(d[78]),"+f"(d[79]),"+f"(d[80]),"+f"(d[81]),"+f"(d[82]),"+f"(d[83]),"+f"(d[84]),"+f"(d[85]),"+f"(d[86]),"+f"(d[87]),"+f"(d[88]),"+f"(d[89]),"+f"(d[90]),"+f"(d[91]),"+f"(d[92]),"+f"(d[93]),"+f"(d[94]),"+f"(d[95])
    : "l"(da), "l"(db), "r"(acc)); } };
template<> struct WSS<32,1,1> { static __device__ __forceinline__ void mma(float* d, uint64_t da, uint64_t db, int acc = 1) {
  asm volatile("{\n.reg .pred p;\nsetp.ne.b32 p, %18, 0;\nwgmma.mma_async.sync.aligned.m64n32k16.f32.bf16.bf16 {%0,%1,%2,%3,%4,%5,%6,%7,%8,%9,%10,%11,%12,%13,%14,%15}, %16, %17, p, 1, 1, 1, 1;\n}"
    : "+f"(d[0]),"+f"(d[1]),"+f"(d[2]),"+f"(d[3]),"+f"(d[4]),"+f"(d[5]),"+f"(d[6]),"+f"(d[7]),"+f"(d[8]),"+f"(d[9]),"+f"(d[10]),"+f"(d[11]),"+f"(d[12]),"+f"(d[13]),"+f"(d[14]),"+f"(d[15])
    : "l"(da), "l"(db), "r"(acc)); } };
template<> struct WSS<128,0,1> { static __device__ __forceinline__ void mma(float* d, uint64_t da, uint64_t db, int acc = 1) {
  asm volatile("{\n.reg .pred p;\nsetp.ne.b32 p, %66, 0;\nwgmma.mma_async.sync.aligned.m64n128k16.f32.bf16.bf16 {%0,%1,%2,%3,%4,%5,%6,%7,%8,%9,%10,%11,%12,%13,%14,%15,%16,%17,%18,%19,%20,%21,%22,%23,%24,%25,%26,%27,%28,%29,%30,%31,%32,%33,%34,%35,%36,%37,%38,%39,%40,%41,%42,%43,%44,%45,%46,%47,%48,%49,%50,%51,%52,%53,%54,%55,%56,%57,%58,%59,%60,%61,%62,%63}, %64, %65, p, 1, 1, 0, 1;\n}"
    : "+f"(d[0]),"+f"(d[1]),"+f"(d[2]),"+f"(d[3]),"+f"(d[4]),"+f"(d[5]),"+f"(d[6]),"+f"(d[7]),"+f"(d[8]),"+f"(d[9]),"+f"(d[10]),"+f"(d[11]),"+f"(d[12]),"+f"(d[13]),"+f"(d[14]),"+f"(d[15]),"+f"(d[16]),"+f"(d[17]),"+f"(d[18]),"+f"(d[19]),"+f"(d[20]),"+f"(d[21]),"+f"(d[22]),"+f"(d[23]),"+f"(d[24]),"+f"(d[25]),"+f"(d[26]),"+f"(d[27]),"+f"(d[28]),"+f"(d[29]),"+f"(d[30]),"+f"(d[31]),"+f"(d[32]),"+f"(d[33]),"+f"(d[34]),"+f"(d[35]),"+f"(d[36]),"+f"(d[37]),"+f"(d[38]),"+f"(d[39]),"+f"(d[40]),"+f"(d[41]),"+f"(d[42]),"+f"(d[43]),"+f"(d[44]),"+f"(d[45]),"+f"(d[46]),"+f"(d[47]),"+f"(d[48]),"+f"(d[49]),"+f"(d[50]),"+f"(d[51]),"+f"(d[52]),"+f"(d[53]),"+f"(d[54]),"+f"(d[55]),"+f"(d[56]),"+f"(d[57]),"+f"(d[58]),"+f"(d[59]),"+f"(d[60]),"+f"(d[61]),"+f"(d[62]),"+f"(d[63])
    : "l"(da), "l"(db), "r"(acc)); } };
template<> struct WSS<96,0,1> { static __device__ __forceinline__ void mma(float* d, uint64_t da, uint64_t db, int acc = 1) {
  asm volatile("{\n.reg .pred p;\nsetp.ne.b32 p, %50, 0;\nwgmma.mma_async.sync.aligned.m64n96k16.f32.bf16.bf16 {%0,%1,%2,%3,%4,%5,%6,%7,%8,%9,%10,%11,%12,%13,%14,%15,%16,%17,%18,%19,%20,%21,%22,%23,%24,%25,%26,%27,%28,%29,%30,%31,%32,%33,%34,%35,%36,%37,%38,%39,%40,%41,%42,%43,%44,%45,%46,%47}, %48, %49, p, 1, 1, 0, 1;\n}"
    : "+f"(d[0]),"+f"(d[1]),"+f"(d[2]),"+f"(d[3]),"+f"(d[4]),"+f"(d[5]),"+f"(d[6]),"+f"(d[7]),"+f"(d[8]),"+f"(d[9]),"+f"(d[10]),"+f"(d[11]),"+f"(d[12]),"+f"(d[13]),"+f"(d[14]),"+f"(d[15]),"+f"(d[16]),"+f"(d[17]),"+f"(d[18]),"+f"(d[19]),"+f"(d[20]),"+f"(d[21]),"+f"(d[22]),"+f"(d[23]),"+f"(d[24]),"+f"(d[25]),"+f"(d[26]),"+f"(d[27]),"+f"(d[28]),"+f"(d[29]),"+f"(d[30]),"+f"(d[31]),"+f"(d[32]),"+f"(d[33]),"+f"(d[34]),"+f"(d[35]),"+f"(d[36]),"+f"(d[37]),"+f"(d[38]),"+f"(d[39]),"+f"(d[40]),"+f"(d[41]),"+f"(d[42]),"+f"(d[43]),"+f"(d[44]),"+f"(d[45]),"+f"(d[46]),"+f"(d[47])
    : "l"(da), "l"(db), "r"(acc)); } };
template<> struct WSS<64,0,1> { static __device__ __forceinline__ void mma(float* d, uint64_t da, uint64_t db, int acc = 1) {
  asm volatile("{\n.reg .pred p;\nsetp.ne.b32 p, %34, 0;\nwgmma.mma_async.sync.aligned.m64n64k16.f32.bf16.bf16 {%0,%1,%2,%3,%4,%5,%6,%7,%8,%9,%10,%11,%12,%13,%14,%15,%16,%17,%18,%19,%20,%21,%22,%23,%24,%25,%26,%27,%28,%29,%30,%31}, %32, %33, p, 1, 1, 0, 1;\n}"
    : "+f"(d[0]),"+f"(d[1]),"+f"(d[2]),"+f"(d[3]),"+f"(d[4]),"+f"(d[5]),"+f"(d[6]),"+f"(d[7]),"+f"(d[8]),"+f"(d[9]),"+f"(d[10]),"+f"(d[11]),"+f"(d[12]),"+f"(d[13]),"+f"(d[14]),"+f"(d[15]),"+f"(d[16]),"+f"(d[17]),"+f"(d[18]),"+f"(d[19]),"+f"(d[20]),"+f"(d[21]),"+f"(d[22]),"+f"(d[23]),"+f"(d[24]),"+f"(d[25]),"+f"(d[26]),"+f"(d[27]),"+f"(d[28]),"+f"(d[29]),"+f"(d[30]),"+f"(d[31])
    : "l"(da), "l"(db), "r"(acc)); } };
template<> struct WSS<8,1,0> { static __device__ __forceinline__ void mma(float* d, uint64_t da, uint64_t db, int acc = 1) {
  asm volatile("{\n.reg .pred p;\nsetp.ne.b32 p, %6, 0;\nwgmma.mma_async.sync.aligned.m64n8k16.f32.bf16.bf16 {%0,%1,%2,%3}, %4, %5, p, 1, 1, 1, 0;\n}"
    : "+f"(d[0]),"+f"(d[1]),"+f"(d[2]),"+f"(d[3])
    : "l"(da), "l"(db), "r"(acc)); } };
__device__ __forceinline__ void wrs128_first(float* d, const uint32_t* a, uint64_t db) {
  asm volatile("wgmma.mma_async.sync.aligned.m64n128k16.f32.bf16.bf16 {%0,%1,%2,%3,%4,%5,%6,%7,%8,%9,%10,%11,%12,%13,%14,%15,%16,%17,%18,%19,%20,%21,%22,%23,%24,%25,%26,%27,%28,%29,%30,%31,%32,%33,%34,%35,%36,%37,%38,%39,%40,%41,%42,%43,%44,%45,%46,%47,%48,%49,%50,%51,%52,%53,%54,%55,%56,%57,%58,%59,%60,%61,%62,%63}, {%64,%65,%66,%67}, %68, 0, 1, 1, 0;"
    : "=f"(d[0]),"=f"(d[1]),"=f"(d[2]),"=f"(d[3]),"=f"(d[4]),"=f"(d[5]),"=f"(d[6]),"=f"(d[7]),"=f"(d[8]),"=f"(d[9]),"=f"(d[10]),"=f"(d[11]),"=f"(d[12]),"=f"(d[13]),"=f"(d[14]),"=f"(d[15]),"=f"(d[16]),"=f"(d[17]),"=f"(d[18]),"=f"(d[19]),"=f"(d[20]),"=f"(d[21]),"=f"(d[22]),"=f"(d[23]),"=f"(d[24]),"=f"(d[25]),"=f"(d[26]),"=f"(d[27]),"=f"(d[28]),"=f"(d[29]),"=f"(d[30]),"=f"(d[31]),"=f"(d[32]),"=f"(d[33]),"=f"(d[34]),"=f"(d[35]),"=f"(d[36]),"=f"(d[37]),"=f"(d[38]),"=f"(d[39]),"=f"(d[40]),"=f"(d[41]),"=f"(d[42]),"=f"(d[43]),"=f"(d[44]),"=f"(d[45]),"=f"(d[46]),"=f"(d[47]),"=f"(d[48]),"=f"(d[49]),"=f"(d[50]),"=f"(d[51]),"=f"(d[52]),"=f"(d[53]),"=f"(d[54]),"=f"(d[55]),"=f"(d[56]),"=f"(d[57]),"=f"(d[58]),"=f"(d[59]),"=f"(d[60]),"=f"(d[61]),"=f"(d[62]),"=f"(d[63])
    : "r"(a[0]), "r"(a[1]), "r"(a[2]), "r"(a[3]), "l"(db)); }
__device__ __forceinline__ void wrs96_first(float* d, const uint32_t* a, uint64_t db) {
  asm volatile("wgmma.mma_async.sync.aligned.m64n96k16.f32.bf16.bf16 {%0,%1,%2,%3,%4,%5,%6,%7,%8,%9,%10,%11,%12,%13,%14,%15,%16,%17,%18,%19,%20,%21,%22,%23,%24,%25,%26,%27,%28,%29,%30,%31,%32,%33,%34,%35,%36,%37,%38,%39,%40,%41,%42,%43,%44,%45,%46,%47}, {%48,%49,%50,%51}, %52, 0, 1, 1, 0;"
    : "=f"(d[0]),"=f"(d[1]),"=f"(d[2]),"=f"(d[3]),"=f"(d[4]),"=f"(d[5]),"=f"(d[6]),"=f"(d[7]),"=f"(d[8]),"=f"(d[9]),"=f"(d[10]),"=f"(d[11]),"=f"(d[12]),"=f"(d[13]),"=f"(d[14]),"=f"(d[15]),"=f"(d[16]),"=f"(d[17]),"=f"(d[18]),"=f"(d[19]),"=f"(d[20]),"=f"(d[21]),"=f"(d[22]),"=f"(d[23]),"=f"(d[24]),"=f"(d[25]),"=f"(d[26]),"=f"(d[27]),"=f"(d[28]),"=f"(d[29]),"=f"(d[30]),"=f"(d[31]),"=f"(d[32]),"=f"(d[33]),"=f"(d[34]),"=f"(d[35]),"=f"(d[36]),"=f"(d[37]),"=f"(d[38]),"=f"(d[39]),"=f"(d[40]),"=f"(d[41]),"=f"(d[42]),"=f"(d[43]),"=f"(d[44]),"=f"(d[45]),"=f"(d[46]),"=f"(d[47])
    : "r"(a[0]), "r"(a[1]), "r"(a[2]), "r"(a[3]), "l"(db)); }

constexpr int IMG = 1792;
struct Scratch {
  unsigned cnt[32 * 32];
  float modp[2 * 3200];
  float gb[640];
  uint4 vt[8 * 224];
  uint2 st3[128 * 64];
  uint4 T[640 * 256];
  uint4 Y[640 * 256];
  uint4 z2n[4 * 32 * IMG];
};
__device__ __align__(1024) Scratch g_scr;
enum { C_A = 0, C_Y = 10, C_M = 20, C_G = 22, C_H = 24  , C_E = 28 };

constexpr uint32_t SM_R = 81920, SM_PO = 184320, SM_S = 212992, SM_X1 = 221184, SM_TAIL = 229376, SM_TOTAL = 232448;
constexpr uint32_t KV_V = 7168;
constexpr uint32_t SM_VT = SM_S, SM_LN1 = SM_S, SM_MOD = SM_S + 3584, SM_LN2 = SM_S + 6144, SM_SILU = SM_LN2;
constexpr uint32_t SM_BAR = SM_TAIL, SM_TPC = SM_BAR + 912, SM_DUMMY = SM_TPC + 48, SM_LNB = SM_DUMMY + 64, SM_PROF = SM_LNB + 1024, SM_ONE = SM_PROF + 512, SM_GB = SM_MOD;
static_assert(SM_ONE + 128 <= SM_TOTAL, "smem");
__device__ __forceinline__ uint32_t offU(int s) { return SM_R + ((0x64302u >> (4 * s)) & 15) * 16384; }
__device__ __forceinline__ uint32_t offX(int s) { return s < 2 ? SM_X1 + s * 4096 : SM_R - 36864 + s * 32768; }
__device__ __forceinline__ uint32_t offF(int s) { return offU(s) + 4208; }
__host__ __device__ constexpr uint32_t placeB(int st) { return ((uint32_t)(0x9874245000ull >> (8 * st)) & 255) * 1024; }
__host__ __device__ constexpr uint32_t placeA(int st) { return ((uint32_t)(0x40906C1CD8ull >> (8 * st)) & 255) * 1024; }
__device__ __forceinline__ int nstart(int n) { return n < 3 ? 224 * n : 640; }
enum {
  B_KV = 0, B_F = 5, B_WM = 10, B_Q = 15, B_U = 20, B_YH = 25  , B_AP = 31, B_LN = 36  , B_PP = 38  ,
  B_G0 = 41, B_VT = 42, B_X1D = 45, B_CP = 46, B_ACK = 43, B_GB = 44, B_LOK = 47  ,
  B_FULL1 = 50, B_FULL2 = 54,
  B_KVF = 64, B_EMPTY1 = 69, B_EMPTY2 = 73, B_VAL = 78, B_PST = 83  , B_VTF = 85, B_PUB = 86, B_Z1S = 87, B_PFREE = 88, B_NIL = 89,
  B_DONE = 90  , B_AO = 94, B_LNB = 99, B_RF = 100, B_MT = 105, B_WMF = 106, B_FO = 107, B_G1 = 112
};

struct Params {
  const __nv_bfloat16 *k, *v, *ssmk;
  Scratch* g;
  const __nv_bfloat16* shiftk;
  int by_sm;
  const __nv_bfloat16 *c, *ssmD, *bsp, *wout, *wsp;
  uint8_t tile[64];
};

struct Maps { CUtensorMap k, v, f, wm, q, y, w2, x1, wsp, out, wo, wm2, w3, wn; };

__device__ __forceinline__ void mbar_arrive(uint32_t a) { asm volatile("mbarrier.arrive.shared::cta.b64 _, [%0];" ::"r"(a) : "memory"); }
__device__ __forceinline__ void mbar_expect(uint32_t a, int b) { asm volatile("mbarrier.arrive.expect_tx.shared::cta.b64 _, [%0], %1;" ::"r"(a), "r"(b) : "memory"); }
__device__ __forceinline__ void mbar_wait(uint32_t a, int ph) {
  asm volatile("{\n.reg .pred p;\nWL:\nmbarrier.try_wait.parity.shared::cta.b64 p, [%0], %1;\n@!p bra WL;\n}" ::"r"(a), "r"(ph) : "memory");
}
__device__ __forceinline__ void mbar_wait2(uint32_t a, uint32_t b, int pa, int pb) {
  asm volatile("{\n.reg .pred p, q;\nWL:\nmbarrier.try_wait.parity.shared::cta.b64 p, [%0], %2;\nmbarrier.try_wait.parity.shared::cta.b64 q, [%1], %3;\nand.pred p, p, q;\n@!p bra WL;\n}" ::"r"(a), "r"(b), "r"(pa), "r"(pb) : "memory");
}
__device__ __forceinline__ uint32_t mbar_test(uint32_t a, int ph) {
  uint32_t r;
  asm volatile("{\n.reg .pred p;\nmbarrier.test_wait.parity.shared::cta.b64 p, [%1], %2;\nselp.u32 %0, 1, 0, p;\n}" : "=r"(r) : "r"(a), "r"(ph) : "memory");
  return r;
}
__device__ __forceinline__ void mbar_wait_b(uint32_t a, int ph) {
  asm volatile("{\n.reg .pred p;\n.reg .u32 c;\nmov.u32 c, 0;\nWL:\nmbarrier.try_wait.parity.shared::cta.b64 p, [%0], %1;\n@p bra WD;\n"
               "add.u32 c, c, 1;\nsetp.lt.u32 p, c, 0x10000;\n@p bra WL;\ntrap;\nWD:\n}" ::"r"(a), "r"(ph) : "memory");
}
__device__ __forceinline__ uint32_t mapa(uint32_t a, uint32_t rank) { uint32_t r; asm("mapa.shared::cluster.u32 %0, %1, %2;" : "=r"(r) : "r"(a), "r"(rank)); return r; }
__device__ __forceinline__ void bar_sync(int id, int n) { asm volatile("bar.sync %0, %1;" ::"r"(id), "r"(n) : "memory"); }
__device__ __forceinline__ void bar_arrive(int id, int n) { asm volatile("bar.arrive %0, %1;" ::"r"(id), "r"(n) : "memory"); }
__device__ __forceinline__ unsigned ld_acquire(const void* p) { unsigned v; asm volatile("ld.acquire.gpu.global.u32 %0, [%1];" : "=r"(v) : "l"(p) : "memory"); return v; }
__device__ __forceinline__ unsigned ld_relaxed(const void* p) { unsigned v; asm volatile("ld.relaxed.gpu.global.u32 %0, [%1];" : "=r"(v) : "l"(p) : "memory"); return v; }
__device__ __forceinline__ uint4 ld_relaxed4(const void* p) { uint4 v; asm volatile("ld.relaxed.gpu.global.v4.u32 {%0,%1,%2,%3}, [%4];" : "=r"(v.x), "=r"(v.y), "=r"(v.z), "=r"(v.w) : "l"(p) : "memory"); return v; }
__device__ __forceinline__ void st_relaxed4(void* p, uint4 v) { asm volatile("st.relaxed.gpu.global.v4.u32 [%0], {%1,%2,%3,%4};" ::"l"(p), "r"(v.x), "r"(v.y), "r"(v.z), "r"(v.w) : "memory"); }
__device__ __forceinline__ uint2 ld_relaxed2(const void* p) { uint2 v; asm volatile("ld.relaxed.gpu.global.v2.u32 {%0,%1}, [%2];" : "=r"(v.x), "=r"(v.y) : "l"(p) : "memory"); return v; }
__device__ __forceinline__ void st_relaxed2(void* p, uint32_t a, uint32_t b) { asm volatile("st.relaxed.gpu.global.v2.u32 [%0], {%1,%2};" ::"l"(p), "r"(a), "r"(b) : "memory"); }
__device__ __forceinline__ void st_relaxed(void* p, unsigned v) { asm volatile("st.relaxed.gpu.global.u32 [%0], %1;" ::"l"(p), "r"(v) : "memory"); }
__device__ __forceinline__ void fence_gpu() { asm volatile("fence.acq_rel.gpu;" ::: "memory"); }
__device__ __forceinline__ void wait_cnt(const unsigned* c, unsigned target) {
#pragma unroll 1
  while (__any_sync(0xffffffffu, (int)(ld_relaxed(c) - target) < 0)) {}
}
__device__ __forceinline__ void fence_async_g() { asm volatile("fence.proxy.async.global;" ::: "memory"); }
__device__ __forceinline__ void fence_async_s() { asm volatile("fence.proxy.async.shared::cta;" ::: "memory"); }
#define ELECT "{\n.reg .pred e;\nelect.sync _|e, 0xffffffff;\n@e "
__device__ __forceinline__ void w_expect(uint32_t a, int b) { asm volatile(ELECT "mbarrier.arrive.expect_tx.shared::cta.b64 _, [%0], %1;\n}" ::"r"(a), "r"(b) : "memory"); }
__device__ __forceinline__ void bulk_g2s(uint32_t dst, const void* src, int bytes, uint32_t bar) {
  asm volatile(ELECT "cp.async.bulk.shared::cluster.global.mbarrier::complete_tx::bytes [%0], [%1], %2, [%3];\n}" ::"r"(dst), "l"(src), "r"(bytes), "r"(bar) : "memory");
}
__device__ __forceinline__ void bulk_commit() { asm volatile("cp.async.bulk.commit_group;" ::: "memory"); }
__device__ __forceinline__ void bulk_wait_read0() { asm volatile("cp.async.bulk.wait_group.read 0;" ::: "memory"); }
__device__ __forceinline__ void tma2d(uint32_t dst, const CUtensorMap* m, int c0, int c1, uint32_t bar) {
  asm volatile(ELECT "cp.async.bulk.tensor.2d.shared::cluster.global.mbarrier::complete_tx::bytes [%0], [%1, {%3, %4}], [%2];\n}" ::"r"(dst), "l"(m), "r"(bar), "r"(c0), "r"(c1) : "memory");
}
__device__ __forceinline__ void tma3d(uint32_t dst, const CUtensorMap* m, int c0, int c1, int c2, uint32_t bar) {
  asm volatile(ELECT "cp.async.bulk.tensor.3d.shared::cluster.global.mbarrier::complete_tx::bytes [%0], [%1, {%3, %4, %5}], [%2];\n}" ::"r"(dst), "l"(m), "r"(bar), "r"(c0), "r"(c1), "r"(c2) : "memory");
}
__device__ __forceinline__ void tma_rows(uint32_t dst, const CUtensorMap* m, int c0, int c2, int c3, uint32_t bar) {
  if (MCAST) asm volatile(ELECT "cp.async.bulk.tensor.4d.shared::cluster.global.mbarrier::complete_tx::bytes.multicast::cluster [%0], [%1, {%3, %6, %4, %5}], [%2], %7;\n}" ::"r"(dst), "l"(m), "r"(bar), "r"(c0), "r"(c2), "r"(c3), "r"(0), "h"((uint16_t)3) : "memory");
  else asm volatile(ELECT "cp.async.bulk.tensor.4d.shared::cluster.global.mbarrier::complete_tx::bytes [%0], [%1, {%3, %6, %4, %5}], [%2];\n}" ::"r"(dst), "l"(m), "r"(bar), "r"(c0), "r"(c2), "r"(c3), "r"(0) : "memory");
}
__device__ __forceinline__ void tma_rows_add(const CUtensorMap* m, int c0, int c2, int c3, uint32_t src) {
  asm volatile(ELECT "cp.reduce.async.bulk.tensor.4d.global.shared::cta.add.tile.bulk_group [%0, {%2, %5, %3, %4}], [%1];\n}" ::"l"(m), "r"(src), "r"(c0), "r"(c2), "r"(c3), "r"(0) : "memory");
}
__device__ __forceinline__ void tma5d(uint32_t dst, const CUtensorMap* m, int c0, int c1, int c2, int c3, uint32_t bar) {
  asm volatile(ELECT "cp.async.bulk.tensor.5d.shared::cluster.global.mbarrier::complete_tx::bytes [%0], [%1, {%3, %4, %5, %6, %7}], [%2];\n}" ::"r"(dst), "l"(m), "r"(bar), "r"(c0), "r"(c1), "r"(c2), "r"(c3), "r"(0) : "memory");
}
__device__ __forceinline__ void tma5d_store(const CUtensorMap* m, int c0, int c2, int c3, uint32_t src) {
  asm volatile(ELECT "cp.async.bulk.tensor.5d.global.shared::cta.bulk_group [%0, {%2, %5, %3, %4, %5}], [%1];\n}" ::"l"(m), "r"(src), "r"(c0), "r"(c2), "r"(c3), "r"(0) : "memory");
}
__device__ __forceinline__ void bulk_s2peer(uint32_t rdst, uint32_t src, int bytes, uint32_t rbar) {
  asm volatile(ELECT "cp.async.bulk.shared::cluster.shared::cta.mbarrier::complete_tx::bytes [%0], [%1], %2, [%3];\n}" ::"r"(rdst), "r"(src), "r"(bytes), "r"(rbar) : "memory");
}
__device__ __forceinline__ void w_count(const Scratch* G, int idx) { asm volatile(ELECT "red.relaxed.gpu.global.add.u32 [%0], 1;\n}" ::"l"(G->cnt + idx * 32) : "memory"); }
__device__ __forceinline__ void w_count_timed(const Scratch* G, int idx) {
  asm volatile("{\n.reg .pred e;\n.reg .u64 t;\nelect.sync _|e, 0xffffffff;\nmov.u64 t, %%globaltimer;\n@e red.relaxed.gpu.global.max.u64 [%0+8], t;\n@e red.relaxed.gpu.global.add.u32 [%0], 1;\n}" ::"l"(G->cnt + idx * 32) : "memory");
}
__device__ __forceinline__ void w_arrive(uint32_t a) { asm volatile(ELECT "mbarrier.arrive.shared::cta.b64 _, [%0];\n}" ::"r"(a) : "memory"); }
__device__ __forceinline__ void w_arrive_peer(uint32_t ra) { asm volatile(ELECT "mbarrier.arrive.shared::cluster.b64 _, [%0];\n}" ::"r"(ra) : "memory"); }
__device__ __forceinline__ void tmap_prefetch(const CUtensorMap* m) { asm volatile("prefetch.tensormap [%0];" ::"l"(m) : "memory"); }
__device__ __forceinline__ uint64_t mkdesc(uint32_t addr, uint32_t lbo, uint32_t sbo, uint32_t swz) {
  return (uint64_t)((addr & 0x3FFFF) >> 4) | ((uint64_t)(lbo >> 4) << 16) | ((uint64_t)(sbo >> 4) << 32) | ((uint64_t)swz << 62);
}
#define WG_FENCE() asm volatile("wgmma.fence.sync.aligned;" ::: "memory")
#define WG_COMMIT() asm volatile("wgmma.commit_group.sync.aligned;" ::: "memory")
#define WG_WAIT(n) asm volatile("wgmma.wait_group.sync.aligned " #n ";" ::: "memory")
__device__ __forceinline__ uint32_t lds32(uint32_t a) { uint32_t v; asm volatile("ld.shared.u32 %0, [%1];" : "=r"(v) : "r"(a) : "memory"); return v; }
__device__ __forceinline__ uint2 lds64(uint32_t a) { uint2 v; asm volatile("ld.shared.v2.u32 {%0,%1}, [%2];" : "=r"(v.x), "=r"(v.y) : "r"(a) : "memory"); return v; }
__device__ __forceinline__ uint4 lds128(uint32_t a) { uint4 v; asm volatile("ld.shared.v4.u32 {%0,%1,%2,%3}, [%4];" : "=r"(v.x), "=r"(v.y), "=r"(v.z), "=r"(v.w) : "r"(a) : "memory"); return v; }
__device__ __forceinline__ float4 lds128f(uint32_t a) { float4 v; asm volatile("ld.shared.v4.f32 {%0,%1,%2,%3}, [%4];" : "=f"(v.x), "=f"(v.y), "=f"(v.z), "=f"(v.w) : "r"(a) : "memory"); return v; }
__device__ __forceinline__ void sts32(uint32_t a, uint32_t v) { asm volatile("st.shared.u32 [%0], %1;" ::"r"(a), "r"(v) : "memory"); }
__device__ __forceinline__ void sts64(uint32_t a, uint32_t x, uint32_t y) { asm volatile("st.shared.v2.u32 [%0], {%1,%2};" ::"r"(a), "r"(x), "r"(y) : "memory"); }
__device__ __forceinline__ void sts128(uint32_t a, uint4 v) { asm volatile("st.shared.v4.u32 [%0], {%1,%2,%3,%4};" ::"r"(a), "r"(v.x), "r"(v.y), "r"(v.z), "r"(v.w) : "memory"); }
__device__ __forceinline__ void stsm4(uint32_t a, uint32_t r0, uint32_t r1, uint32_t r2, uint32_t r3) {
  asm volatile("stmatrix.sync.aligned.m8n8.x4.shared.b16 [%0], {%1,%2,%3,%4};" ::"r"(a), "r"(r0), "r"(r1), "r"(r2), "r"(r3) : "memory");
}
__device__ __forceinline__ void stsm4t(uint32_t a, uint32_t r0, uint32_t r1, uint32_t r2, uint32_t r3) {
  asm volatile("stmatrix.sync.aligned.m8n8.x4.trans.shared.b16 [%0], {%1,%2,%3,%4};" ::"r"(a), "r"(r0), "r"(r1), "r"(r2), "r"(r3) : "memory");
}
__device__ __forceinline__ void ldsm4(uint32_t a, uint32_t& r0, uint32_t& r1, uint32_t& r2, uint32_t& r3) {
  asm volatile("ldmatrix.sync.aligned.m8n8.x4.shared.b16 {%0,%1,%2,%3}, [%4];" : "=r"(r0), "=r"(r1), "=r"(r2), "=r"(r3) : "r"(a) : "memory");
}
__device__ __forceinline__ void ldsm4t(uint32_t a, uint32_t& r0, uint32_t& r1, uint32_t& r2, uint32_t& r3) {
  asm volatile("ldmatrix.sync.aligned.m8n8.x4.trans.shared.b16 {%0,%1,%2,%3}, [%4];" : "=r"(r0), "=r"(r1), "=r"(r2), "=r"(r3) : "r"(a) : "memory");
}
__device__ __forceinline__ void hmma(float* d, uint32_t a0, uint32_t a1, uint32_t a2, uint32_t a3, uint32_t b0, uint32_t b1) {
  asm volatile("mma.sync.aligned.m16n8k16.row.col.f32.bf16.bf16.f32 {%0,%1,%2,%3}, {%4,%5,%6,%7}, {%8,%9}, {%0,%1,%2,%3};"
               : "+f"(d[0]), "+f"(d[1]), "+f"(d[2]), "+f"(d[3]) : "r"(a0), "r"(a1), "r"(a2), "r"(a3), "r"(b0), "r"(b1));
}
__device__ __forceinline__ void stg32_if(bool on, void* p, uint32_t v) {
  asm volatile("{\n.reg .pred p;\nsetp.ne.b32 p, %2, 0;\n@p st.global.u32 [%0], %1;\n}" ::"l"(p), "r"(v), "r"((int)on) : "memory");
}
__device__ __forceinline__ void ldg128_if(bool on, const void* p, uint32_t* v) {
  asm volatile("{\n.reg .pred p;\nsetp.ne.b32 p, %5, 0;\n@p ld.relaxed.gpu.global.v4.u32 {%0,%1,%2,%3}, [%4];\n}" : "=r"(v[0]), "=r"(v[1]), "=r"(v[2]), "=r"(v[3]) : "l"(p), "r"((int)on) : "memory");
}
__device__ __forceinline__ void sts32(uint32_t a, uint32_t v, bool on) { if (on) sts32(a, v); }
__device__ __forceinline__ void ldsm4_if(bool on, uint32_t a, uint32_t* v) {
  asm volatile("{\n.reg .pred p;\nsetp.ne.b32 p, %5, 0;\n@p ldmatrix.sync.aligned.m8n8.x4.shared.b16 {%0,%1,%2,%3}, [%4];\n}" : "+r"(v[0]), "+r"(v[1]), "+r"(v[2]), "+r"(v[3]) : "r"(a), "r"((int)on) : "memory");
}
__device__ __forceinline__ void lds32_if(bool on, uint32_t& v, uint32_t a) {
  asm volatile("{\n.reg .pred p;\nsetp.ne.b32 p, %2, 0;\n@p ld.shared.u32 %0, [%1];\n}" : "=r"(v) : "r"(a), "r"((int)on) : "memory");
}
__device__ __forceinline__ void st_peer4(uint32_t ra, const uint4* v, uint32_t rbar) {
#define SP(o, a, b, c, d) "st.async.weak.shared::cluster.mbarrier::complete_tx::bytes.v4.b32 [%0+" #o "], {%" #a ",%" #b ",%" #c ",%" #d "}, [%1];\n"
  asm volatile(SP(0, 2, 3, 4, 5) SP(512, 6, 7, 8, 9) SP(1024, 10, 11, 12, 13) SP(1536, 14, 15, 16, 17)
               ::"r"(ra), "r"(rbar), "r"(v[0].x), "r"(v[0].y), "r"(v[0].z), "r"(v[0].w), "r"(v[1].x), "r"(v[1].y), "r"(v[1].z), "r"(v[1].w),
                 "r"(v[2].x), "r"(v[2].y), "r"(v[2].z), "r"(v[2].w), "r"(v[3].x), "r"(v[3].y), "r"(v[3].z), "r"(v[3].w) : "memory");
}
__device__ __forceinline__ uint32_t ldg32(const void* p) { uint32_t v; asm volatile("ld.global.nc.u32 %0, [%1];" : "=r"(v) : "l"(p)); return v; }
__device__ __forceinline__ uint32_t ldg16(const void* p) { uint16_t v; asm volatile("ld.global.nc.u16 %0, [%1];" : "=h"(v) : "l"(p)); return v; }
__device__ __forceinline__ uint32_t pack2(float lo, float hi) { uint32_t d; asm("cvt.rn.bf16x2.f32 %0, %1, %2;" : "=r"(d) : "f"(hi), "f"(lo)); return d; }
__device__ __forceinline__ float blo(uint32_t x) { return __uint_as_float(x << 16); }
__device__ __forceinline__ float bhi(uint32_t x) { return __uint_as_float(x & 0xffff0000u); }
__device__ __forceinline__ float bround(float x) { return bhi(pack2(0.f, x)); }
__device__ __forceinline__ uint32_t bmul2(uint32_t a, uint32_t b) { uint32_t d; asm("mul.rn.bf16x2 %0, %1, %2;" : "=r"(d) : "r"(a), "r"(b)); return d; }
__device__ __forceinline__ uint32_t badd2(uint32_t a, uint32_t b) { uint32_t d; asm("add.rn.bf16x2 %0, %1, %2;" : "=r"(d) : "r"(a), "r"(b)); return d; }
__device__ __forceinline__ uint32_t bfma2(uint32_t a, uint32_t b, uint32_t c) { uint32_t d; asm("fma.rn.bf16x2 %0, %1, %2, %3;" : "=r"(d) : "r"(a), "r"(b), "r"(c)); return d; }
__device__ __forceinline__ float silu(float x) { return __fdividef(x, 1.f + __expf(-x)); }
__device__ __forceinline__ float gelu2(float a, float k1, float k2) {
  float u, t;
  asm volatile("mul.rn.f32 %0, %1, %1;" : "=f"(u) : "f"(a));
  asm("tanh.approx.f32 %0, %1;" : "=f"(t) : "f"(a * fmaf(u, k2, k1)));
  asm volatile("fma.rn.f32 %0, %0, %1, %0;" : "+f"(a) : "f"(t));
  return a;
}
__device__ __forceinline__ void stage_end() { asm volatile("pmevent 1;"); }
__device__ __forceinline__ uint32_t bdup(uint32_t x, int hi) {
  uint32_t d;
  if (hi) asm("{\n.reg .b16 l, h;\nmov.b32 {l, h}, %1;\nmov.b32 %0, {h, h};\n}" : "=r"(d) : "r"(x));
  else asm("{\n.reg .b16 l, h;\nmov.b32 {l, h}, %1;\nmov.b32 %0, {l, l};\n}" : "=r"(d) : "r"(x));
  return d;
}
__device__ __forceinline__ uint32_t baffine(uint32_t x, uint32_t c) {
  uint32_t d;
  asm("{\n.reg .b16 l, h;\n.reg .b32 a, b;\nmov.b32 {l, h}, %2;\nmov.b32 a, {l, l};\nmov.b32 b, {h, h};\nfma.rn.bf16x2 %0, %1, a, b;\n}" : "=r"(d) : "r"(x), "r"(c));
  return d;
}
__device__ __forceinline__ uint32_t clk32() { uint32_t t; asm volatile("mov.u32 %0, %%clock;" : "=r"(t)::"memory"); return t; }
__device__ __forceinline__ void sleep_until(uint32_t t0) {
  asm volatile("{\n.reg .pred p;\n.reg .s32 t;\nSL:\nmov.u32 t, %%clock;\nsub.s32 t, t, %0;\nsetp.lt.s32 p, t, 0;\n@p nanosleep.u32 20;\n@p bra.uni SL;\n}" ::"r"(t0) : "memory");
}
__device__ __forceinline__ void sleep_for(uint32_t d) { sleep_until(__shfl_sync(0xffffffffu, clk32() + d + (threadIdx.x & 31), 0)); }

#define TSP(mask, on, id) do {} while (0)
#define TSX(mask, id) do {} while (0)
#define TGX(id) do {} while (0)
#define FX(id) do {} while (0)
#define TS1(id) TSX(1, id)
#define TS2(id) TSX(2, id)
#define TS3(id) TSX(4, id)
#define TSS(id) TSX(7, id)
#define W0(id) (w == 0 ? (id) : 127)

template <int N>
__device__ __forceinline__ void bfly(float* v, int lane, int mask) {
  const bool b = lane & mask;
#pragma unroll
  for (int i = 0; i < N / 2; i++) {
    float mine = b ? v[i + N / 2] : v[i], other = b ? v[i] : v[i + N / 2];
    v[i] = mine + __shfl_xor_sync(0xffffffffu, other, mask);
  }
}
__device__ __forceinline__ float quad_sum(float x) { x += __shfl_xor_sync(0xffffffffu, x, 1); return x + __shfl_xor_sync(0xffffffffu, x, 2); }

template <int N>
__device__ __forceinline__ void conv_tri(float* acc, uint32_t (*A)[4], uint64_t db) {
  if constexpr (N == 128) wrs128_first(acc, A[0], db); else WRS<N>::mma(acc, A[0], db);
  if constexpr (N > 16) conv_tri<N - 16>(acc, A + 1, db + 16);
}
__device__ __forceinline__ void conv_mma(float* acc, uint32_t (*A)[4], uint64_t db) {
  WG_FENCE();
  conv_tri<128>(acc, A + 8, db + 128);
  WG_COMMIT();
  WG_FENCE();
  WRS<128>::mma(acc, A[7], db + 112); WRS<128>::mma(acc, A[6], db + 96);
  WG_COMMIT();
  WG_WAIT(1);
  WG_FENCE();
  conv_tri<128>(acc + 64, A, db + 128);
#pragma unroll
  for (int T = 5; T >= 0; T--) WRS<128>::mma(acc, A[T], db + 16 * T);
  WG_COMMIT();
}
template <int N>
__device__ __forceinline__ void zero_acc(float* a) {
#pragma unroll
  for (int i = 0; i < N; i += 2) asm volatile("mov.b64 {%0, %1}, 0;" : "=f"(a[i]), "=f"(a[i + 1]));
}
template <int N>
__device__ __forceinline__ void undef(float* a) {
#pragma unroll
  for (int i = 0; i < N; i++) asm volatile("" : "=f"(a[i]));
}
__device__ __forceinline__ uint32_t ext_frag(float mu, float sg, int q) {
  const float mh = bround(-mu), sh = bround(sg);
  const float lo = q == 0 ? mh : q == 1 ? -mu - mh : sh, hi = q == 0 ? mh : q == 1 ? sh : sg - sh;
  return pack2(lo, hi) & (q == 3 ? 0u : ~0u);
}
__device__ __forceinline__ uint32_t opaque(uint32_t x) { asm volatile("" : "+r"(x)); return __shfl_sync(0xffffffffu, x, 0); }
__device__ __forceinline__ uint32_t tagw(uint32_t x, uint32_t par) { return (x & ~1u) | par; }
__device__ __forceinline__ uint32_t bitsel(uint32_t x, uint32_t y, uint32_t mask) { return (x & ~mask) | (y & mask); }
__device__ __forceinline__ uint32_t stale(uint32_t acc, uint32_t x, uint32_t par) { uint32_t d; asm("lop3.b32 %0, %1, %2, %3, 0xf6;" : "=r"(d) : "r"(acc), "r"(x), "r"(par)); return d; }
__device__ __forceinline__ bool any_stale(uint32_t acc) { return __builtin_expect(__any_sync(0xffffffffu, acc & 1), 0); }
__device__ __forceinline__ uint32_t sum2(uint32_t a, uint32_t b, uint32_t c, uint32_t d) { return pack2(__uint_as_float(a) + __uint_as_float(b), __uint_as_float(c) + __uint_as_float(d)); }
__device__ __forceinline__ uint32_t ln3(float s, float q, float eps) {
  const float mu = s * (1.f / 864.f), c = rsqrtf(fmaxf(q * (1.f / 864.f) - mu * mu, 0.f) + eps);
  return pack2(c, -mu * c);
}
__device__ __forceinline__ void refetch(uint32_t ta, const uint4* gp, uint32_t wo, uint32_t par) {
  bool again;
#pragma unroll 1
  do { again = any_stale(lds32(ta + wo) ^ par); sts128(ta, ld_relaxed4(gp)); sts128(ta + 16, ld_relaxed4(gp + 1)); } while (again);
  fence_async_s();
}

__global__ void __cluster_dims__(2, 1, 1) __launch_bounds__(512, 1)
fused_kernel(const __grid_constant__ Params p, const __grid_constant__ Maps tm) {
  extern __shared__ __align__(1024) unsigned char smem_raw[];
  const uint32_t tstart = __shfl_sync(0xffffffffu, clk32() + (threadIdx.x & 31), 0);
  const uint32_t sb = __shfl_sync(0xffffffffu, (uint32_t)__cvta_generic_to_shared(smem_raw), 0);
  const int tid = threadIdx.x, lane = tid & 31;
  const int warp = __shfl_sync(0xffffffffu, tid >> 5, 0);
  const int wg = warp >> 2, w = warp & 3, t128 = tid & 127;
  const int r = lane >> 2, q = lane & 3, mi = lane >> 3, rr = lane & 7;
  Scratch* const G = p.g;
  auto BAR = [&](int i) { return sb + SM_BAR + i * 8; };
  if (warp == 15) asm volatile("{\n.reg .u32 t;\nld.relaxed.gpu.global.u32 t, [%0];\nshr.u32 t, t, 6;\nredux.sync.min.u32 t, t, 0xffffffff;\nadd.u32 t, t, 1;\nst.shared.u32 [%1], t;\n}"
                               ::"l"(G->cnt + min(lane, C_E + 1) * 32), "r"(sb + SM_TPC + 4) : "memory");
  unsigned crank, mytpc;
  asm("mov.u32 %0, %%smid;" : "=r"(mytpc));
  asm("mov.u32 %0, %%cluster_ctarank;" : "=r"(crank));
  mytpc = (p.by_sm ? mytpc : blockIdx.x) >> 1;
  const int bid = (mytpc < 60 ? mytpc : mytpc < 62 ? mytpc + 4 : mytpc - 2) * 2 + crank;
  if (wg == 1) asm volatile("barrier.cluster.arrive.relaxed.aligned;" ::: "memory");
  if (warp >= 4 && warp < 10 && bid < 128) {
    const int i = warp < 8 ? warp - 2 : warp - 8, it = (int)(SEQ0 >> (8 * i)), s = it & 15;
    const __nv_bfloat16* a = (&p.k)[(it >> 4) & 3] + ((it & 32) ? (s * 128 + bid) * 2048 + lane * 64 : ((bid >> 1) * 32 + lane) * 640 + s * 128 + crank * 64);
    if (i > 2) asm volatile(ELECT "prefetch.tensormap [%0];\n}" ::"l"(&tm.k + (5 - i)) : "memory");
    if (i > 1) sleep_until(tstart + T_2 - 2 * PACE_D + i * PACE_D);
    asm volatile("prefetch.global.L2 [%0];" ::"l"(a));
  }
#define BI(o) "@e mbarrier.init.shared::cta.b64 [%0+" #o "], %1;\n"
  if (warp == 12 && bid < 128) {
    asm volatile("{\n.reg .pred e;\nelect.sync _|e, 0xffffffff;\n" BI(0) "fence.mbarrier_init.release.cluster;\n}" ::"r"(BAR(B_KV)), "r"(1) : "memory");
    w_expect(BAR(B_KV), 11520 + 5120);
    tma5d(sb, &tm.k, crank * 64, 0, (bid >> 1) * 4 - 1, 0, BAR(B_KV));
    tma5d(sb + KV_V, &tm.v, crank * 64, 0, (bid >> 1) * 4, 0, BAR(B_KV));
    bulk_g2s(sb + SM_S, p.shiftk, 5120, BAR(B_KV));
  }
  if (warp < 4) {
#pragma unroll 1
    for (int g = warp; g < 16; g += 4)
      asm volatile("{\n.reg .pred e;\nelect.sync _|e, 0xffffffff;\n" BI(8) BI(16) BI(24) BI(32) BI(40) BI(48) BI(56) "fence.mbarrier_init.release.cluster;\n}"
                   ::"r"(BAR(g * 7)), "r"(g < 7 ? (bid >= 128 && !g ? 14 : 1) : g < 9 ? 2 : 4) : "memory");
  }
  if (tid == 96) sts32(sb + SM_TPC, mytpc);
  if (wg != 1) asm volatile("barrier.cluster.arrive.relaxed.aligned;" ::: "memory");
  auto READY = [&]() { asm volatile("barrier.cluster.wait.aligned;" ::: "memory"); };
  auto EPOCH = [&]() { return lds32(sb + SM_TPC + 4); };

  if (bid >= 128) {
    const int j = bid - 128;
    READY();
    constexpr uint32_t S_TAB = SM_S;
    if (warp < 14) {
      const unsigned tag = EPOCH(), par = tag & 1;
      const uint32_t to = sb + S_TAB + (tid >> 2) * 64 + q * 8;
      st_relaxed4(G->vt + (tid < 224 ? j * 224 : (3 + j) * 224) + tid, make_uint4(0, 0, 0, (tag - 1) & 0x3fff));
      if (tid < 192 && j * 192 + tid < 640) st_relaxed(G->gb + j * 192 + tid, par ^ 1);
      if (tid < 160) {
        const uint32_t c0 = ldg32(p.c + (tid >> 2) * 16 + q * 2), c1 = ldg32(p.c + (tid >> 2) * 16 + q * 2 + 8);
        sts64(to + 4096, pack2(silu(blo(c0)), silu(bhi(c0))), pack2(silu(blo(c1)), silu(bhi(c1))));
        sleep_until(tstart + 9000);
        wait_cnt(G->cnt + (C_M + (lane & 1)) * 32, tag * 64u);
        const uint4* mp = (const uint4*)(G->modp + 1920) + tid;
        uint4 a, b, c, d;
#pragma unroll 1
        do {
          a = ld_relaxed4(mp); b = ld_relaxed4(mp + 800); c = ld_relaxed4(mp + 160); d = ld_relaxed4(mp + 960);
        } while (any_stale(stale(stale(stale(a.x ^ par, b.x, par), c.x, par), d.x, par)));
        sts64(to, badd2(sum2(c.x, d.x, c.z, d.z), 0x3f803f80), badd2(sum2(c.y, d.y, c.w, d.w), 0x3f803f80));
        sts64(to + 32, sum2(a.x, b.x, a.z, b.z), sum2(a.y, b.y, a.w, b.w));
      }
      bar_sync(1, 448);
      TSS(warp == 0 ? 10 : 127);
            int st = 0, ph = 0;
#pragma unroll 1
      for (int part = 0; part < 3; part++) {
        float d[2][4] = {{0.f, 0.f, 0.f, 0.f}, {0.f, 0.f, 0.f, 0.f}};
        const int ch = 2 * warp + (mi & 1) + (part < 2 && part == (j == 1) ? 4 : 0);
        const uint32_t ao = sb + (ch >> 3) * 8192 + (rr + (mi >> 1) * 8) * 128 + (((ch & 7) ^ rr) << 4);
#pragma unroll 1
        for (int u = 0; u < 10; u++) {
          uint32_t a[4][4];
          uint2 b[4];
#pragma unroll
          for (int i = 0; i < 4; i++) b[i] = lds64(sb + S_TAB + (part >> 1) * 4096 + (u * 4 + i) * 64 + (r & 1) * 32 + q * 8);
          mbar_wait(BAR(B_FULL1 + st), ph);
#pragma unroll
          for (int i = 0; i < 4; i++) ldsm4t(ao + st * 32768 + i * 2048, a[i][0], a[i][1], a[i][2], a[i][3]);
#pragma unroll
          for (int i = 0; i < 4; i++) hmma(d[i & 1], a[i][0], a[i][1], a[i][2], a[i][3], b[i].x, b[i].y);
          w_arrive(BAR(1 + st));
          if (++st == 6) { st = 0; ph ^= 1; }
        }
#pragma unroll
        for (int i = 0; i < 2; i++) {
          const float a = d[0][2 * i] + d[1][2 * i], b = d[0][2 * i + 1] + d[1][2 * i + 1], ah = bround(a), bh = bround(b);
          const int cc = warp * 16 + i * 8 + r;
          if (q == 0 && part < 2) st_relaxed4(G->vt + (part * 4 + j) * 224 + cc, make_uint4(pack2(ah, a - ah), pack2(ah, bh), pack2(b - bh, bh), tag & 0x3fff));
          if (q == 0 && part == 2 && cc < 192 && j * 192 + cc < 640) st_relaxed(G->gb + j * 192 + cc, __float_as_uint(ah) | par);
        }
        TSS(warp == 0 ? 1 + part : 127);
      }
    } else if (warp == 14) {
      sleep_until(tstart + T_SPARE);
      uint32_t fb = BAR(B_FULL1), dst = sb, ph = 1;
#pragma unroll 1
      for (int part = 0; part < 3; part++) {
        const int c0 = part == 2 ? 50 + j * 3 : ((part ? 0 : 864) + nstart(j)) >> 6;
#pragma unroll 1
        for (int row = 0; row < 640; row += 64) {
          mbar_wait(fb - (B_FULL1 - 1) * 8, ph);
#pragma unroll 1
          for (int x = 0; x < 2; x++) { w_expect(fb, 16384); tma3d(dst + x * 16384, part == 2 ? &tm.wm2 : &tm.w2, 0, row, c0 + x * 2, fb); }
          fb += 8; dst += 32768;
          if (dst == sb + 196608) { fb -= 48; dst = sb; ph ^= 1; }
        }
      }
    } else {
      const unsigned tag = EPOCH();
#pragma unroll 1
      for (int spin = 0; __any_sync(0xffffffffu, (int)(ld_relaxed(G->cnt + (C_E + (lane & 1)) * 32) - tag * 64u) < 0); spin++) { if (spin > (1 << 18)) __trap(); __nanosleep(500); }
    }
    return;
  }
  const int m = p.tile[bid >> 1] >> 1, n = (p.tile[bid >> 1] & 1) * 2 + crank;
  const uint32_t peer = mapa(sb, crank ^ 1) - sb;

  unsigned tag = 0, par = 0;
  if (wg == 3) {
    asm volatile("setmaxnreg.dec.sync.aligned.u32 32;");
    auto pf_wsp = [&](int i) {
      const __nv_bfloat16* a = p.wsp + ((m >> 1) * 128 + (m & 1) * 32 + lane) * 2048 + ((i + ROT * (m >> 3)) & 15) * 128 + (i >> 4) * 64;
      asm volatile("prefetch.global.L2 [%0];\nprefetch.global.L2 [%0+262144];" ::"l"(a));
    };
    if (w == 3) {
      READY();
      TS1(103);
      const unsigned tag = EPOCH();
      TS1(100);
      if (lane < 9) mbar_expect(BAR(B_AP + lane), lane < 5 ? 8192 : lane < 7 ? (lane - 4) * 1024 : 14336);
      if (lane < 10) mbar_expect(BAR(B_U + lane), lane < 5 ? 4096 : 8192);
#pragma unroll 1
      for (int s = 0; s < 5; s++) {
        if (s && lane < 2) tmap_prefetch(&tm.wm + 2 * s - 2 + lane);
        mbar_wait(BAR(s < HINT_A ? B_KV + s : B_KVF + s), 0);
        if (s < NAPS) sleep_for(NAPA);
        wait_cnt(G->cnt + (C_A + 2 * s + (bid >> 6)) * 32, tag * 64u);
        bulk_g2s(sb + offU(s), G->T + (s * 128 + bid) * 256, 4096, BAR(B_U + s));
        TS1(80 + s);
      }
      {
        uint32_t t;
        asm volatile("ld.shared::cluster.u32 %0, [%1];" : "=r"(t) : "r"(sb + SM_TPC + peer) : "memory");
        if (t != mytpc) __trap();
        unsigned todo = 31;
        mbar_wait(BAR(B_WMF), 0);
#pragma unroll 1
        do {
          unsigned rdy = __ballot_sync(0xffffffffu, ((todo >> lane) & 1) && (int)(ld_relaxed(G->cnt + (C_Y + 2 * lane + crank) * 32) - tag * 64u) >= 0);
          todo &= ~rdy;
#pragma unroll 1
          for (; rdy; rdy &= rdy - 1) {
            const int s = __ffs(rdy) - 1;
            tma3d(sb + s * 16384 + (crank ^ 1) * 8192, &tm.y, 0, s * 128 + crank * 64, m * 2, BAR(B_YH + s));
            TS1(85 + s);
          }
        } while (todo);
      }
#pragma unroll 1
      for (int part = 0; part < 2; part++) {
        const uint4* vp = G->vt + (part * 4 + n) * 224;
        if (STOP_AFTER >= 2) mbar_wait2(BAR(part ? B_VTF : B_AO), BAR(B_AO + 1 + H2), 0, 0);
#pragma unroll 1
        while (__any_sync(0xffffffffu, ld_relaxed(&vp[223].w) != (tag & 0x3fff))) {}
        unsigned bad, ph = 1;
#pragma unroll 1
        do {
          w_expect(BAR(B_U + part), 3584); bulk_g2s(sb + (STOP_AFTER >= 2 ? SM_VT : SM_X1), vp, 3584, BAR(B_U + part));
          mbar_wait(BAR(B_U + part), ph);
          ph ^= 1; bad = 0;
#pragma unroll
          for (int k = 0; k < 7; k++) bad |= lds32(sb + (STOP_AFTER >= 2 ? SM_VT : SM_X1) + k * 512 + lane * 16 + 12) ^ tag;
        } while (__any_sync(0xffffffffu, bad & 0x3fff));
        w_arrive(BAR(B_VT));
        TS2(75 + part);
      }
      if (STOP_AFTER >= 2) {
        pf_wsp(20 + n);
        {
          const uint2* sp = G->st3 + m * 256 + 32 + lane;
          uint2 a, b, c, d;
          mbar_wait(BAR(B_G1), 0);
          sleep_for(WAIT1);
#pragma unroll 1
          do { a = ld_relaxed2(sp); b = ld_relaxed2(sp + 64); c = ld_relaxed2(sp + 128); d = ld_relaxed2(sp + 192); } while (any_stale(stale(stale(stale(a.x ^ tag, b.x, tag), c.x, tag), d.x, tag)));
          sts32(sb + SM_LNB + lane * 4, ln3((__uint_as_float(a.x) + __uint_as_float(b.x)) + (__uint_as_float(c.x) + __uint_as_float(d.x)),
                                            (__uint_as_float(a.y) + __uint_as_float(b.y)) + (__uint_as_float(c.y) + __uint_as_float(d.y)), __uint_as_float(lds32(sb + SM_LNB + lane * 4))));
          w_arrive(BAR(B_CP));
          TS2(69);
        }
        mbar_wait2(BAR(B_PUB), BAR(B_X1D), 0, 0);
#pragma unroll 1
        for (int h = 0; h < 2; h++) {
          if (h) { fence_async_g(); fence_gpu(); }
          w_count(G, C_H + 2 * h + crank);
          TS2(77 + h);
          pf_wsp(24 + 4 * h + n);
          sleep_for(POLL1);
#pragma unroll 1
          while (__any_sync(0xffffffffu, (int)(ld_acquire(G->cnt + (C_H + 2 * h + (lane & 1)) * 32) - tag * 64u) < 0)) {}
          w_arrive(BAR(B_LOK + 1 + h));
          TS2(91 + h);
        }
        fence_async_g();
        if (lane == 0) asm volatile("cp.async.bulk.prefetch.L2.global [%0], 8640;" ::"l"(p.wout + bid * 4320) : "memory");
      }
      if (STOP_AFTER >= 4) {
#pragma unroll 1
        for (int s = 0; s < 5; s++) {
          uint2 a;
#pragma unroll 1
          for (;;) { a = ld_relaxed2(G->gb + s * 128 + crank * 64 + lane * 2); if (!any_stale(stale(a.x ^ tag, a.y, tag))) break; __nanosleep(200); }
          sts32(sb + SM_GB + s * 128 + (r >> 2) * 64 + q * 16 + (r & 3) * 4, __byte_perm(a.x, a.y, 0x7632));
        }
        w_arrive(BAR(B_GB));
      }
      goto done;
    }
    if (w == 2) {
      const uint32_t dsk = ldg16(p.ssmD + min(lane, 4) * 128 + bid);
      READY();
#pragma unroll 1
      for (int s = 0; s < 5; s++) {
        const uint32_t fE = sb + offF(s) + 16 + lane * 16, dk = __shfl_sync(0xffffffffu, dsk, s);
        mbar_wait(BAR(B_F + s), 0);
        TSX(17, 70 + s);
#pragma unroll 1
        for (int o = 2048; o >= 0; o -= 2048) {
          uint4 e[4];
          uint32_t nx[4];
#pragma unroll
          for (int i = 0; i < 4; i++) { e[i] = lds128(fE + o + i * 512); nx[i] = lds32(fE + o + i * 512 + 16); }
          if (lane + o == 0) { const uint32_t f0 = pack2(blo(e[0].x) + blo(dk), bhi(e[0].x)); sts32(fE, f0); sts32(fE + 4156, f0 << 16); }
#pragma unroll
          for (int i = 0; i < 4; i++) sts128(fE + o + 4160 + i * 512, make_uint4(__byte_perm(e[i].x, e[i].y, 0x5432), __byte_perm(e[i].y, e[i].z, 0x5432), __byte_perm(e[i].z, e[i].w, 0x5432), __byte_perm(e[i].w, nx[i], 0x5432)));
        }
        asm volatile(ELECT "mbarrier.arrive.shared::cta.b64 _, [%0], 4;\n}" ::"r"(BAR(B_FO + s)) : "memory");
        TS1(75 + s);
      }
    }
    if (w < 2) {
      {
        const int it = (int)(((lane < 8 ? SEQ0 : lane < 16 ? SEQ1 : lane < 24 ? SEQ2 : SEQ3) >> (8 * rr)) & 255), ty = it >> 4, s = it & 15;
        const bool on = lane < 25 && (ty != 3 || bid < 100);
        const uint32_t bi = ty == 4 ? B_Q + (s > 2) : max(ty - 1, 0) * 5 + s;
        const uint32_t a0 = ty == 3 ? (bid >> 1) * 64 + ((crank * 320 + s * 64) << 16) : ty == 2 ? 0 : s * 128 + crank * 64;
        const uint32_t a1 = ty < 2 ? ((bid >> 1) * 4 - 1 + ty) << 8 : ty == 2 ? (s * 128 + bid) << 8 : ty == 3 ? 0 : ((m & ~1) << 8) + (m & 1) * 4;
        const uint32_t a2 = (ty == 2 ? offF(s) + 16 : s * 16384 + (ty < 2 ? ty * KV_V : ((ty ^ crank) & 1) * 8192)) + ty + (bi << 18) + ((B_KVF + s) << 24);
        const uint32_t a3 = tstart + T_2 - 2 * PACE_D + lane * PACE_D + max(lane - 13, 0) * (PACE_F - PACE_D) + min(max(lane - WPOS, 0), 5) * (PACE_W - PACE_F) + max(lane - 20, 0) * (PACE_Q - PACE_F);
        unsigned todo = __ballot_sync(0xffffffffu, on) & (0x55555555u << (2 + w));
        READY();
        if (on && ty != 1 && (it <= 0x40 || it == 0x44) && lane && !w) mbar_expect(BAR(bi), ty == 0 ? 11520 : ty == 2 ? 4096 : ty == 3 ? 8192 : 24576 - s * 2048);
#pragma unroll 1
        while (todo) {
          const int i = __ffs(todo) - 1;
          const uint32_t b0 = __shfl_sync(0xffffffffu, a0, i), b1 = __shfl_sync(0xffffffffu, a1, i), b2 = __shfl_sync(0xffffffffu, a2, i);
          todo &= todo - 1;
          sleep_until(__shfl_sync(0xffffffffu, a3, i));
          TSX(16, 1 + i);
          if ((b2 & 7) > 2) mbar_wait(BAR(b2 >> 24), 0);
          tma5d(sb + (b2 & 0x3ff80), &tm.k + (b2 & 7), b0 & 0xffff, b0 >> 16, (int)b1 >> 8, b1 & 255, BAR((b2 >> 18) & 63));
        }
      }
      TS1(w == 0 ? 95 : 127);
    }
    if (w) {
      const int x = w - 1;
      if (STOP_AFTER >= 2) {
        if (lane == 0) tmap_prefetch(&tm.w3 + x);
        sleep_until(tstart + T_WIN);
#pragma unroll 1
        for (int g = 0; g < 20; g++) {
          const int base = (g < 10 ? 864 : 0) + nstart(n), row = ((g < 10 ? g : g - 10) ^ crank) * 64;
          const uint32_t fb = BAR(B_FULL1 + (g & 3)), dst = sb + SM_R + (g & 3) * 32768;
          mbar_wait(fb + (B_EMPTY1 - B_FULL1) * 8, (g >> 2) & 1);
          if (x) { w_expect(fb, 4096); tma2d(dst + 24576, &tm.wn, base + ((base & 32) ? 0 : 192), row, fb); }
          else { w_expect(fb, 24576); tma3d(dst, &tm.w3, 0, row, (base + 32) >> 6, fb); }
        }
      }
    } else {
      const unsigned tag = lds32(sb + SM_TPC + 4);
      mbar_wait(BAR(B_WMF), 0);
      if (NAPM) sleep_for(NAPM);
      wait_cnt(G->cnt + (C_M + (lane & 1)) * 32, tag * 64u);
      w_arrive(BAR(B_YH + 5));
      TS1(90);
      if (STOP_AFTER >= 2) {
#pragma unroll 1
        for (int s = 0; s < 5; s++) {
          mbar_wait(BAR(B_AO + s), 0);
          pf_wsp(4 * s + n);
        }
        mbar_wait(BAR(B_AP + 4), 0);
#pragma unroll 1
        for (int s = 0; s < 5; s++) {
          tma5d_store(&tm.x1, s * 128 + crank * 64, m & ~1, (m & 1) * 4 + (n & 2), sb + offX(s));
          sleep_for(XGAP);
        }
        bulk_commit();
        asm volatile("cp.async.bulk.wait_group 0;" ::: "memory");
        w_arrive(BAR(B_X1D));
      }
      if (STOP_AFTER >= 3) {
        mbar_wait(BAR(B_G0), 0);
        sleep_for(POLL0);
        TS2(100);
        uint4 c;
#pragma unroll 1
        do c = ld_relaxed4(G->cnt + (C_G + (lane & 1)) * 32); while (__any_sync(0xffffffffu, (int)(c.x - tag * 64u) < 0));
        TS2(101);
#pragma unroll 1
        for (;;) {
          uint32_t t;
          asm volatile("mov.u32 %0, %%globaltimer_lo;" : "=r"(t)::"memory");
          if (__all_sync(0xffffffffu, t - c.z >= DELAY0)) break;
        }
        w_arrive(BAR(B_LOK));
      }
    }
    if (STOP_AFTER >= 3) {
      const uint4* zp = G->z2n + n * 32 * IMG;
      uint32_t off = 0, ph = 0;
      mbar_wait(BAR(w == 1 ? B_X1D : B_LOK), 0);
#pragma unroll 1
      for (int i = 0; i < 32; i++) {
        const int M = (i + ROT * (m >> 3)) & 15;
        const uint32_t fb = BAR(B_FULL2) + off, dst = sb + (((uint32_t)((w == 1 ? 0x40906C1CD8ull : 0x9874245000ull) >> off) & 255) << 10);
        if (i == 16) mbar_wait(BAR(B_LOK + 1), 0);
        mbar_wait(fb + (B_EMPTY2 - B_FULL2) * 8, ph);
        if (!w) { if (i < 10 || i == 16) TS2(min(80 + i, 90)); if (i < 15) TSX(8, 81 + i); }
        if (w == 1) { if (i < 15) TSX(8, 101 + i);
          w_expect(fb, 8192);
          if (MCAST) {
            w_arrive_peer(BAR(B_KV) + off + peer);
            mbar_wait(BAR(B_KV) + off, ph ^ 1);
          }
          tma_rows(dst + MCAST * crank * 4096, &tm.wsp, M * 128 + (i >> 4) * 64, m & ~1, (m & 1) * 4 + MCAST * crank * 2, fb);
        }
        else if ((i & 1) * 2 == w) { w_expect(fb, 28672); bulk_g2s(dst, zp + ((i & 16) + M) * IMG, 28672, fb); }
        off += 8;
        if (off == 40) { off = 0; ph ^= 1; }
      }
    }
    if (w) {
      const int x = w - 1;
      if (STOP_AFTER >= 4) {
#pragma unroll 1
        for (int k = 0; k < 10; k++) {
          const int st = 1 + ((k + 1) & 3);
          const uint32_t fb = BAR(B_FULL2 + st);
          mbar_wait(fb + (B_EMPTY2 - B_FULL2) * 8, ((k + 1) >> 2) & 1);
          TS3(x ? 127 : 60 + k);
          w_expect(fb, 14336);
          tma2d(sb + placeB(st) + x * 14336, &tm.wo, (k < 8 ? ((k ^ (n & BOXX)) & 2) + x : 4) * 128 + crank * 64, nstart(n ^ (k < 8 ? k >> 2 : k & 1)) + 112 * (k < 8 ? k & 1 : x), fb);
        }
      }
    } else {
      if (STOP_AFTER >= 4) mbar_wait(BAR(B_GB), 0);
      w_count(G, C_E + crank);
      if (STOP_AFTER >= 4) {
        mbar_wait_b(BAR(B_PFREE), 0);
#pragma unroll 1
        for (int e = 0; e < 2; e++) {
          mbar_wait_b(BAR(B_PST + max(e, PONE)), 0);
          if (e) { mbar_wait_b(BAR(B_EMPTY2 + PGATE), 1); sleep_for(100); }
          bulk_s2peer(sb + e * 14336 + peer, sb + SM_PO + e * 14336, 14336, BAR(B_PP + e) + peer);
        }
        mbar_wait_b(BAR(B_PP), 0);
        TS3(24);
        mbar_wait_b(BAR(B_PP + 1), 0);
        TS3(25);
        w_arrive_peer(BAR(B_ACK) + peer);
        mbar_wait_b(BAR(B_ACK), 0);
      }
      w_arrive(BAR(B_DONE + 3));
#pragma unroll 1
      for (int i = 3; i >= 0; i--) mbar_wait_b(BAR(B_DONE + i), 0);
      return;
    }
    goto done;
  }
  if (wg < 2) {
    sleep_until(tstart + T_AB);
    asm volatile("setmaxnreg.inc.sync.aligned.u32 192;");
    READY();
    tag = EPOCH(); par = tag & 1;
    {
      const uint32_t lofs = (r & 1) ? (16 + 4 * (4 * w + ((r - 1) >> 1) - q)) : (16 + 4160 + 4 * (4 * w + (r >> 1) - 1 - q));
      const uint32_t pl = sb + SM_R + (5 + 2 * wg) * 16384, pa = pl + w * 4096 + ((255 - lane) ^ ((~lane & 8) >> 1)) * 16;
      uint32_t pg[4];
#pragma unroll
      for (int i = 0; i < 4; i++) { const uint32_t x = ((t128 & 112) + (lane & 1) * 8 + ((lane & 15) >> 1) - i) & 255; pg[i] = (x ^ ((x & 8) >> 1)) * 16; }
      if (lane < w) sts128(pa, make_uint4(0, 0, 0, 0));
      if (2 * w < 4 + wg) {
        const uint32_t ub = sb + offU(2 * w + 1 - wg);
        sts32(ub + 4096 + lane * 4, 0);
        if (lane < 3) sts32(ub + 8368 + lane * 4, 0);
      }
      if (warp == 7) sts32(sb + SM_ONE + lane * 4, 0x3f803f80);
      if (tid < 160) { const uint32_t c = ldg32(p.c + crank * 320 + tid * 2); sts32(sb + SM_SILU + tid * 4, pack2(silu(blo(c)), silu(bhi(c)))); }
      fence_async_s();
      bar_sync(6, 256);
      if (!wg) {
        w_arrive(BAR(B_MT));
        if (q < 2) st_relaxed2(G->st3 + ((m * 4 + n) * 2 + q) * 32 + w * 8 + r, par ^ 1, 0);
      }
      const uint32_t p0 = lane < w ? sb + SM_DUMMY + lane * 16 : pa, uo = t128 * 32 + r * 4;
      uint4* yp = G->Y + ((1 - wg) * 128 + bid) * 256 + t128;
      uint32_t A[16][4];
      auto frag = [&](bool on, uint32_t fa, int T) {
#pragma unroll
        for (int i = 0; i < 4; i++) lds32_if(on, A[T][i], fa + T * 256 + (i & 1) * 128 + (i & 2) * 32);
      };
      mbar_wait(BAR(B_FO + 1 - wg), 0);
#pragma unroll
      for (int T = 0; T < 16; T++) frag(true, sb + offF(1 - wg) + lofs, T);
#pragma unroll 1
      for (int s = 1 - wg;; s += 2) {
        float acc[128];
        const uint32_t ub = sb + offU(s), fa = sb + offF(s + 2) + lofs;
        mbar_wait(BAR(B_U + s), 0);
        const uint32_t ut = lds32(ub + uo);
        if (any_stale(ut ^ par)) { FX(118); refetch(ub + (uo & ~31), G->T + (s * 128 + bid) * 256 + (uo >> 5) * 2, uo & 31, par); }
        if (s) bar_sync(10 + wg, 256); else bar_sync(5, 128);
        TSP(1, w == 0, 10 + s);
        conv_mma(acc, A, mkdesc(ub, 64, 128, 0));
        bar_arrive(11 - wg, 256);
        mbar_wait(BAR(B_FO + min(s + 2, 4)), 0);
        WG_WAIT(0);
        TSP(1, w == 0, 15 + s);
#pragma unroll
        for (int x = 7; x >= 0; x--) {
          frag(s < 3, fa, x);
          uint32_t pk[4];
#pragma unroll
          for (int i = 0; i < 4; i++) {
            const int jj = 4 * x + i;
            float lo = acc[4 * jj], hi = acc[4 * jj + 1];
            if (jj < 31) { lo += acc[4 * jj + 6]; hi += acc[4 * jj + 7]; }
            pk[i] = pack2(lo, hi);
          }
          stsm4t(x ? pa - x * 512 : p0, pk[0], pk[1], pk[2], pk[3]);
        }
        bar_sync(4 + wg, 128);
        TSP(1, w == 0, 20 + s);
        uint4 v[8];
        auto gather = [&]() {
#pragma unroll
          for (int i = 0; i < 8; i++) v[i] = lds128(pl + (i & 3) * 4096 + (pg[i & 3] ^ ((i >> 2) * 2048)));
        };
        auto finish = [&]() {
          if (w == 1) w_count(G, C_Y + 2 * s + (bid >> 6));
#pragma unroll
          for (int e = 0; e < 2; e++) {
            const uint4 a = v[4 * e], b = v[4 * e + 1], c = v[4 * e + 2], d = v[4 * e + 3];
            yp[e * 128] = make_uint4(tagw(badd2(badd2(a.x, b.x), badd2(c.x, d.x)), par), badd2(badd2(a.y, b.y), badd2(c.y, d.y)), badd2(badd2(a.z, b.z), badd2(c.z, d.z)), badd2(badd2(a.w, b.w), badd2(c.w, d.w)));
          }
          yp += 256 * 256;
          w_arrive(BAR(s > 0 ? B_EMPTY1 - 1 + s : B_NIL));
          TSP(1, w == 0, 30 + s);
        };
        if (s >= 3) {
          const int t = min(t128, 64 + (t128 & 15));
          const uint4* mp = (const uint4*)G->modp + (t >> 4) * 32 + crank * 16 + (t & 15);
          uint32_t u[8][4];
          auto fetch = [&](bool on) {
#pragma unroll
            for (int i = 0; i < 8; i++) ldg128_if(on, mp + (i & 1) * 800 + ((i >> 1) + (i >= 6)) * 160, u[i]);
          };
          if (!wg) mbar_wait(BAR(B_YH + 5), 0);
          TSP(1, warp == 0, 61);
          fetch(warp < 3);
          gather();
          finish();
          if (warp < 3) {
#pragma unroll 1
            while (any_stale(stale(stale(stale(u[0][0] ^ par, u[1][0], par), u[2][0], par), u[3][0], par) | stale(stale(stale(u[4][0] ^ par, u[5][0], par), u[6][0], par), u[7][0], par))) fetch(true);
#pragma unroll
            for (int f = 0; f < 4; f += 2) {
              auto sum = [&](int v) { return sum2(u[v][f], u[v + 1][f], u[v][f + 1], u[v + 1][f + 1]); };
              sts128(sb + SM_MOD + (t >> 3) * 256 + (t & 3) * 64 + (t & 4) * 4 + f * 16, make_uint4(bmul2(sum(4), badd2(sum(2), 0x3f803f80)), bmul2(sum(4), sum(0)), badd2(sum(6), 0x3f803f80), 0));
            }
          }
          break;
        }
        gather();
#pragma unroll
        for (int T = 8; T < 16; T++) frag(true, fa, T);
        finish();
      }
    }
    if (!wg) { w_arrive(BAR(B_MT)); TSP(1, w == 0, 63); goto gemm; }
    asm volatile("setmaxnreg.dec.sync.aligned.u32 96;");
  } else {
    asm volatile("setmaxnreg.dec.sync.aligned.u32 96;");
    {
      uint32_t ad[8], mk[4];
#pragma unroll
      for (int x = 0; x < 8; x++) ad[x] = sb + q * 1280 + (((2 * w + (r >> 2)) ^ ((2 * q + x) & 7)) << 4) + (r & 3) * 4;
      const int pc = 255 - (bid >> 1) * 4 - q;
#pragma unroll
      for (int i = 0; i < 4; i++) mk[i] = ((pc >> 3) & 7) == (pc & 1) * 4 + i ? 0x10001u : 0u;
      uint4* d = G->T + (crank * 64 + (t128 >> 2) * 2) * 256 + pc;
      TSP(1, w == 0, 111);
      READY();
      par = EPOCH() & 1;
#pragma unroll 1
      for (int s = 0; s < 5; s++) {
        const uint32_t so = s * 16384;
        mbar_wait(BAR(B_KV + s), 0);
        TSP(1, w == 0, 1 + s); TSP(16, w == 0, 60 + s);
        if (HINT_A && s < HINT_A && w == 1) w_count(G, C_A + 2 * s + crank);
        const uint4 sk = lds128(sb + SM_S + (so >> 4) + crank * 512 + (t128 >> 2) * 16);
        uint32_t kk[11], o[8];
#pragma unroll
        for (int i = 0; i < 11; i++) kk[i] = i < 3 ? lds32(ad[i + 5] + so + (i + 5) * 128) : lds32(ad[(i - 1) & 7] + so + (i + 7) * 128);
#pragma unroll
        for (int i = 0; i < 8; i++) o[i] = lds32(ad[i] + so + KV_V + i * 128);
        const uint32_t w0 = __byte_perm(sk.x, sk.z, 0x5410), w1 = __byte_perm(sk.x, sk.z, 0x7632), w2 = __byte_perm(sk.y, sk.w, 0x5410), w3 = __byte_perm(sk.y, sk.w, 0x7632);
#pragma unroll
        for (int i = 0; i < 8; i++) o[i] = bmul2(bfma2(kk[i + 3], w0, bfma2(kk[i + 2], w1, bfma2(kk[i + 1], w2, bmul2(kk[i], w3)))), o[i]);
#pragma unroll
        for (int i = 0; i < 4; i++) o[2 * i + 1] = bitsel(o[2 * i + 1], par * 0x10001u, mk[i]);
        d[s * 32768] = make_uint4(__byte_perm(o[1], o[0], 0x5410), __byte_perm(o[3], o[2], 0x5410), __byte_perm(o[5], o[4], 0x5410), __byte_perm(o[7], o[6], 0x5410));
        d[s * 32768 + 256] = make_uint4(__byte_perm(o[1], o[0], 0x7632), __byte_perm(o[3], o[2], 0x7632), __byte_perm(o[5], o[4], 0x7632), __byte_perm(o[7], o[6], 0x7632));
        {
          if (HINT_A < 5 && s >= HINT_A && w == 1) w_count(G, C_A + 2 * s + crank);
          w_arrive(BAR(B_KVF + s));
          TSP(1, w == 0, 40 + s);
        }
      }
    }
    if (bid < 100) {
      float d[16];
      zero_acc<16>(d);
      mbar_wait(BAR(B_MT), 0);
#pragma unroll 1
      for (int s = 0; s < 5; s++) {
        const uint64_t da = mkdesc(sb + s * 16384 + (crank ^ 1) * 8192, 0, 1024, 1), db = mkdesc(sb + SM_SILU + s * 128, 16, 128, 0);
        mbar_wait(BAR(B_WM + s), 0);
        TSP(16, w == 0, 80 + s);
        WG_FENCE();
#pragma unroll
        for (int i = 0; i < 4; i++) WSS<8, 1, 0>::mma(d + i * 4, da + i * 128, db + i * 2);
        WG_COMMIT();
      }
      TSP(1, w == 0, 50);
      if (HINT_M && w == 1) w_count(G, C_M + crank);
      WG_WAIT(0);
      if (q == 0) st_relaxed2(G->modp + crank * 3200 + (bid >> 1) * 64 + w * 16 + r * 2, tagw(__float_as_uint((d[0] + d[4]) + (d[8] + d[12])), par), __float_as_uint((d[2] + d[6]) + (d[10] + d[14])));
    }
    if (w == 1 && (!HINT_M || bid >= 100)) w_count(G, C_M + crank);
    w_arrive(BAR(B_WMF));
    TSP(1, w == 0, 51);
    {
      const uint32_t qb = sb + crank * 8192 + (w * 16 + (lane & 15)) * 128 + (((lane >> 4) ^ rr) << 4);
      float red[4] = {0.f, 0.f, 0.f, 0.f};
#pragma unroll
      for (int s = 0; s < 5; s++) {
        uint32_t x[4][4];
        if (s == 0 || s == 3) { mbar_wait(BAR(B_Q + (s & 1)), 0); TSP(17, w == 0, 55 + (s & 1)); }
#pragma unroll
        for (int i = 0; i < 4; i++) ldsm4((qb ^ (i * 32)) + s * 16384, x[i][0], x[i][1], x[i][2], x[i][3]);
#pragma unroll
        for (int h = 0; h < 2; h++) {
          uint32_t su = badd2(x[0][h], x[0][h + 2]), sq = bfma2(x[0][h], x[0][h], bmul2(x[0][h + 2], x[0][h + 2]));
#pragma unroll
          for (int i = 1; i < 4; i++) { su = badd2(su, badd2(x[i][h], x[i][h + 2])); sq = bfma2(x[i][h], x[i][h], bfma2(x[i][h + 2], x[i][h + 2], sq)); }
          red[2 * h] += blo(su) + bhi(su); red[2 * h + 1] += blo(sq) + bhi(sq);
        }
      }
      TSP(1, w == 0, 57);
      bfly<4>(red, lane, 2);
      red[0] += __shfl_xor_sync(0xffffffffu, red[0], 1); red[1] += __shfl_xor_sync(0xffffffffu, red[1], 1);
      const uint32_t to = (q & 1) * peer;
      asm volatile("st.async.weak.shared::cluster.mbarrier::complete_tx::bytes.v2.f32 [%0], {%1, %2}, [%3];"
                   ::"r"(sb + SM_LN1 + ((q >> 1) * 32 + w * 8 + (r & 1) * 4 + (r >> 1)) * 16 + crank * 8 + to), "f"(red[0]), "f"(red[1]), "r"(BAR(B_LN) + to) : "memory");
      TSP(1, w == 0, 60);
    }
  }
  if (STOP_AFTER >= 2) {
    const int a = w & 1, c = w >> 1;
    const uint32_t qa = rr * 128 + ((4 * c ^ rr) << 4) + mi * 2048 + a * 1024, aa = a * 4096 + (32 * c + r) * 64 + ((q ^ (r >> 1)) << 4);
    uint32_t rs[4], ms[4];
    {
      {
        mbar_wait(BAR(B_LN), 0);
        const float4 u = lds128f(sb + SM_LN1 + a * 512 + lane * 16);
        const float mu = (u.x + u.z) * (1.f / 640.f), rq = rsqrtf(fmaxf((u.y + u.w) * (1.f / 640.f) - mu * mu, 0.f) + 1e-5f);
        const uint32_t pk = pack2(rq, -mu * rq);
#pragma unroll
        for (int j = 0; j < 4; j++) {
          const uint32_t e = __shfl_sync(0xffffffffu, pk, 8 * j + q), o = __shfl_sync(0xffffffffu, pk, 8 * j + 4 + q);
          rs[j] = __byte_perm(e, o, 0x5410); ms[j] = __byte_perm(e, o, 0x7632);
        }
        mbar_wait(BAR(B_MT), 1);
        TS1(wg == 2 ? W0(62) : 127);
      }
      uint32_t su[4] = {}, sq[4] = {};
#pragma unroll 1
      for (int s = (wg & 1) * (1 + H2); s < 5; s += (H2 && !s) ? 1 : 2) {
        const uint32_t own = sb + s * 16384 + crank * 8192;
        uint32_t x[4][4];
        mbar_wait(BAR(B_YH + s), 0);
        if (CHAIN && s > H2) bar_sync(1 + wg, 256);
        if (s == 4) TSP(2, w == 0, 99);
#pragma unroll
        for (int i = 0; i < 4; i++) ldsm4t(own + (qa ^ (i * 16)), x[i][0], x[i][1], x[i][2], x[i][3]);
        {
          const uint4 t0 = lds128(sb + SM_MOD + s * 512 + c * 256 + r * 32), t1 = lds128(sb + SM_MOD + s * 512 + c * 256 + r * 32 + 16);
          uint4 y[4];
#pragma unroll
          for (int i = 0; i < 4; i++) y[i] = lds128(sb + s * 16384 + (crank ^ 1) * 8192 + aa + i * 512);
          stage_end();
          TSP(2, w == 0, 1 + s);
#pragma unroll 1
          while (any_stale(stale(stale(stale(y[0].x ^ par, y[1].x, par), y[2].x, par), y[3].x, par))) {
            FX(120);
            int l;
            asm volatile("mov.u32 %0, %%laneid;" : "=r"(l));
#pragma unroll
            for (int i = 0; i < 4; i++) y[i] = ld_relaxed4(G->Y + (s * 128 + crank * 64 + c * 32 + i * 8 + (l >> 2)) * 256 + m * 8 + a * 4 + (l & 3));
          }
          if (CHAIN && s < 4 && s >= H2) bar_arrive(4 - wg, 256);
          w_arrive_peer(BAR(B_RF + s) + peer);
          bar_sync(wg == 1 ? 5 : 1, 128);
          TSP(2, w == 0, 10 + s);
#pragma unroll
          for (int i = 0; i < 4; i++) {
            const uint32_t yv[4] = {y[i].x, y[i].y, y[i].z, y[i].w};
            const uint32_t ca = bdup(i < 2 ? t0.x : t1.x, i & 1), sa = bdup(i < 2 ? t0.y : t1.y, i & 1), cb = bdup(i < 2 ? t0.z : t1.z, i & 1);
#pragma unroll
            for (int j = 0; j < 4; j++) x[i][j] = bfma2(bfma2(bfma2(x[i][j], rs[j], ms[j]), ca, sa), yv[j], x[i][j]);
            y[i] = make_uint4(bmul2(x[i][0], cb), bmul2(x[i][1], cb), bmul2(x[i][2], cb), bmul2(x[i][3], cb));
            sts128(own + aa + i * 512, y[i]);
          }
          const uint32_t rf = mbar_test(BAR(B_RF + s), 0);
          if (a == n >> 1) {
            uint32_t xs = sb + offX(s) - (mi + a) * 1024;
            asm volatile("" : "+r"(xs));
#pragma unroll
            for (int i = 0; i < 4; i++) stsm4t(xs + (qa ^ (i * 16)), x[i][0], x[i][1], x[i][2], x[i][3]);
          }
          if (s == 2) TSP(2, w == 0, 97);
          fence_async_s();
          w_arrive(BAR(B_AO + s));
          TSP(2, w == 0, 20 + s);
          if (any_stale(~rf)) mbar_wait(BAR(B_RF + s), 0);
          st_peer4(own + aa + peer, y, BAR(B_AP + s) + peer);
        }
        if (s == 2) TSP(2, w == 0, 98);
#pragma unroll
        for (int j = 0; j < 4; j++) {
          su[j] = badd2(su[j], badd2(badd2(x[0][j], x[1][j]), badd2(x[2][j], x[3][j])));
          sq[j] = badd2(sq[j], bfma2(x[3][j], x[3][j], bfma2(x[2][j], x[2][j], bfma2(x[1][j], x[1][j], bmul2(x[0][j], x[0][j])))));
        }
      }
      const uint32_t lb = sb + SM_LNB + w * 256 + lane * 8;
      uint2 u = make_uint2(0, 0);
      if (wg == 2 - H2) { mbar_wait(BAR(B_LNB), 0); u = lds64(lb); }
      float red[8];
#pragma unroll
      for (int k = 0; k < 4; k++) {
        const uint32_t lo = (k & 1) ? sq[k >> 1] : su[k >> 1], hi = (k & 1) ? sq[2 + (k >> 1)] : su[2 + (k >> 1)];
        const uint32_t mine = (lane & 16) ? hi : lo, other = __shfl_xor_sync(0xffffffffu, (lane & 16) ? lo : hi, 16);
        red[(k >> 1) * 4 + (k & 1)] = blo(mine) + blo(other); red[(k >> 1) * 4 + 2 + (k & 1)] = bhi(mine) + bhi(other);
      }
      bfly<8>(red, lane, 8); bfly<4>(red, lane, 4);
      if (wg == 1 + H2) { sts64(lb, __float_as_uint(red[0]), __float_as_uint(red[1])); w_arrive(BAR(B_LNB)); }
      else {
        const uint32_t la = sb + SM_LN2 + (a * 16 + (q >> 1) * 8 + r) * 64 + (q & 1) * 8 + (crank * 2 + c) * 16;
#pragma unroll
        for (int i = 0; i < 2; i++)
          asm volatile("st.async.weak.shared::cluster.mbarrier::complete_tx::bytes.v2.f32 [%0], {%1, %2}, [%3];" ::"r"(la + i * peer), "f"(red[0] + __uint_as_float(u.x)), "f"(red[1] + __uint_as_float(u.y)), "r"(BAR(B_LN + 1) + i * peer) : "memory");
        TSP(2, w == 0, 30);
      }
    }
  }
  if (wg == 2) {
    if (STOP_AFTER >= 3) {
      const uint32_t to = t128 * 32 + r * 4;
      uint32_t off = 0, ph = 0;
#pragma unroll 1
      for (int i = 0; i < 32; i++) {
        const uint32_t tb = sb + (((uint32_t)(0x9874245000ull >> off) & 255) << 10), vb = BAR(B_VAL) + off;
        mbar_wait(vb - (B_VAL - B_FULL2) * 8, ph);
        if (i < 15) TSP(8, w == 0, 41 + i);
        uint32_t v[7];
#pragma unroll
        for (int k = 0; k < 7; k++) v[k] = lds32(tb + to + k * 4096);
        off += 8;
        if (off == 40) { off = 0; ph ^= 1; }
        if (any_stale(stale(stale(stale(v[0] ^ par, v[1], par), v[2], par), v[3], par) | stale(stale(v[4] ^ par, v[5], par), v[6], par))) {
          FX(121);
#pragma unroll 1
          for (int k = 0; k < 7; k++) refetch(tb + (to & ~31) + k * 4096, G->z2n + (n * 32 + (i & 16) + ((i + ROT * (m >> 3)) & 15)) * IMG + k * 256 + t128 * 2, r * 4, par);
        }
        w_arrive(vb);
        if (i < 15) TSP(8, w == 0, 61 + i);
      }
    }
    goto done;
  }
  asm volatile("setmaxnreg.inc.sync.aligned.u32 192;");
gemm:
  {
    if (STOP_AFTER >= 2) {
      const uint32_t za = sb + SM_PO + (mi >> 1) * 1024 + (16 * w + (mi & 1) * 8 + rr) * 16;
      const bool shifted = !wg ^ (n == 1);
      const int R0 = (m >> 1) * 128 + (m & 1) * 32 + w * 8 + r;
      const uint32_t bs0 = q ? 0 : ldg16(p.bsp + R0), bs1 = q ? 0 : ldg16(p.bsp + R0 + 64);
      float k10, k11, sg0 = 0.f, sg1 = 0.f;
      uint32_t zb[28] = {};
      const uint2* sp = G->st3 + (m * 4 + q) * 64 + w * 8 + r;
      uint2 s3 = make_uint2(0, 0);
      uint32_t* const px = (uint32_t*)(G->z2n + (n * 32 + (m >> 1)) * IMG + (shifted ? 256 : 0) + (m & 1) * 32 + w * 8) + lane;
      uint32_t* const py = px - (shifted ? 7168 : 0);
      auto put = [&](bool on, int h, int j, uint32_t v) { stg32_if(on, (j < 24 ? px : py) + h * 16 * IMG * 4 + j * 256, v); };
      const uint32_t tg = rr == (m & 1) * 4 + w;
      {
        float z[112];
        undef<112>(z);
        float k20, k21;
        {
          bar_sync(wg ? 7 : 10, 256);
#pragma unroll 1
          for (int t = 0; t < 10; t += 2) {
            const int g = wg * 10 + t;
            const uint32_t sx = opaque(sb);
            const uint64_t db = mkdesc(sx + SM_R + (g & 2) * 32768, 8192, 1024, 1), da = mkdesc(sx + t * 8192, 4096, 512, 2), dn = mkdesc(sx + SM_R + (g & 2) * 32768 + 24576, 0, 512, 2);
            const uint32_t fb = BAR(B_FULL1 + (g & 2)), e0 = BAR(t ? B_EMPTY1 + 3 - (g & 2) : B_NIL), x0 = BAR(g == 14 ? B_EMPTY2 : g == 18 ? B_EMPTY2 + 2 : B_NIL), x1 = BAR(g >= 16 ? B_EMPTY2 - 15 + g : B_NIL);
#pragma unroll
            for (int j = 0; j < 2; j++) {
              const uint64_t dx = da + (j ^ crank) * 512;
              mbar_wait2(fb + j * 8, BAR(j ? B_AP : B_AO) + t * 4, (g >> 2) & 1, 0);
              if (GATE > 0 && j == (GATE & 1) && g == 10 + (GATE & ~1)) bar_sync(8, 256);
              TSP(2, w == 0, 40 + g + j);
              WG_FENCE();
#pragma unroll
              for (int i = 0; i < 4; i++) WSS<32, 1, 1>::mma(z + 96, dx + i * 64, dn + j * 2048 + i * 64, i || j || t);
#pragma unroll
              for (int i = 0; i < 4; i++) WSS<192, 1, 1>::mma(z, dx + i * 64, db + j * 2048 + i * 128, i || j || t);
              WG_COMMIT();
              WG_WAIT(1);
              if (lane == 0) { mbar_arrive(j ? fb + (B_EMPTY1 - B_FULL1) * 8 : e0); mbar_arrive(j ? x1 : x0); }
            }
          }
          if (!wg && GATE) bar_arrive(7, 256);
          mbar_wait(BAR(B_LN + 1), 0);
          TSP(2, w == 0, 60 + wg);
          const float4 y = lds128f(sb + SM_LN2 + t128 * 16);
          const float m0 = quad_sum(y.x) * (1.f / 640.f), m1 = quad_sum(y.z) * (1.f / 640.f);
          const float v0 = fmaxf(quad_sum(y.y) * (1.f / 640.f) - m0 * m0, 0.f) + 1e-5f, v1 = fmaxf(quad_sum(y.w) * (1.f / 640.f) - m1 * m1, 0.f) + 1e-5f;
          const float h0 = rsqrtf(v0), h1 = rsqrtf(v1);
          sg0 = v0 * h0; sg1 = v1 * h1; k10 = h0 * 0.7978845608028f; k11 = h1 * 0.7978845608028f; k20 = h0 * h0 * h0 * 0.0356774081363f; k21 = h1 * h1 * h1 * 0.0356774081363f;
          const uint32_t ext[4] = {ext_frag(m0, sg0, q), ext_frag(m1, sg1, q), 0u, 0u};
          const uint64_t dv = mkdesc(sb + SM_VT, 0, 128, 0);
          if (wg) mbar_wait(BAR(B_VTF), 0);
          mbar_wait(BAR(B_VT), wg);
          WG_FENCE();
          WRS<32>::mma(z + 96, ext, dv + (shifted ? 0 : 192)); WRS<192>::mma(z, ext, dv + (shifted ? 32 : 0));
          WG_COMMIT();
          if (!wg && GATE >= 0) bar_arrive(GATE ? 8 : 7, 256);
          WG_WAIT(1);
          if (lane == 0) mbar_arrive(BAR(wg ? B_EMPTY2 + 4 : B_EMPTY1 + 1));
          WG_WAIT(0);
          if (wg) bar_sync(5, 128); else if (lane == 0) mbar_arrive(BAR(B_VTF));
          TSP(2, w == 0, 62 + wg);
        }
        if (!wg) {
          uint32_t z0[28];
#pragma unroll
          for (int h = 0; h < 2; h++) {
            float s0, q0, s1, q1, s2, q2;
#pragma unroll
            for (int j = 0; j < 28; j++) {
              if (j == LOAD_AT && h) s3 = ld_relaxed2(sp);
              if (j == PUB_AT && h) {
#pragma unroll 1
                while (any_stale(s3.x ^ par)) { FX(119); s3 = ld_relaxed2(sp); }
                TSP(2, w == 0, 68);
                const uint32_t cp = ln3(quad_sum(__uint_as_float(s3.x)), quad_sum(__uint_as_float(s3.y)), 4e-5f * sg0 * sg0);
#pragma unroll
                for (int i = 0; i < 28; i++) put(true, 0, i, bitsel(baffine(z0[i], cp), par, tg));
                TSP(2, w == 0, 70);
              }
              const float a = gelu2(z[4 * j + 2 * h], h ? k11 : k10, h ? k21 : k20), b = gelu2(z[4 * j + 2 * h + 1], h ? k11 : k10, h ? k21 : k20);
              (h ? zb : z0)[j] = pack2(a, b);
              if (j == 0) { s0 = a; s1 = b; q0 = a * a; q1 = b * b; }
              else { s0 += a; s1 += b; q0 = fmaf(a, a, q0); q1 = fmaf(b, b, q1); }
              if (j == 23) { s2 = s0 + s1; q2 = q0 + q1; }
              if (h && j % PSTEP == PSTEP - 1) stage_end();
            }
            s0 = quad_sum(n == 3 ? s2 : s0 + s1); q0 = quad_sum(n == 3 ? q2 : q0 + q1);
            if (q == n) st_relaxed2((uint2*)sp + h * 32, tagw(__float_as_uint(s0), par), __float_as_uint(q0));
            if (!h && w == 1) { w_count_timed(G, C_G + crank); w_arrive(BAR(B_G0)); }
            TSP(2, w == 0, 64 + h);
            stage_end();
          }
          sts32(sb + SM_LNB + t128, __float_as_uint(4e-5f * sg1 * sg1), q == 0);
          w_arrive(BAR(B_G1));
          if (STOP_AFTER < 3) {
            mbar_wait(BAR(B_CP), 0);
            const uint32_t cp = lds32(sb + SM_LNB + (t128 & ~3));
#pragma unroll
            for (int j = 0; j < 28; j++) put(true, 1, j, bitsel(baffine(zb[j], cp), par, tg));
            w_arrive(BAR(B_PUB));
          }
        } else if (STOP_AFTER >= 3) {
          uint32_t zx = za + (shifted ? 4096 : 0), zy = za - (shifted ? 24576 : 0);
          asm volatile("" : "+r"(zx), "+r"(zy));
#pragma unroll
          for (int j = 0; j < 28; j += 2) stsm4((j < 24 ? zx : zy) + j * 1024, pack2(z[4 * j], z[4 * j + 1]), pack2(z[4 * j + 2], z[4 * j + 3]), pack2(z[4 * j + 4], z[4 * j + 5]), pack2(z[4 * j + 6], z[4 * j + 7]));
          __syncwarp();
          TSP(2, w == 0, 66);
#pragma unroll 1
          for (int j = 0; j < 14; j++) {
            const float cs = n == 3 && j < 2 ? 0.f : 0.5f / 0.7978845608028f, c0 = k10 * cs, c1 = k11 * cs;
            uint32_t v[4];
            ldsm4(za + j * 2048, v[0], v[1], v[2], v[3]);
#pragma unroll
            for (int i = 0; i < 4; i++) v[i] = pack2(gelu2(blo(v[i]), (i & 1) ? k11 : k10, (i & 1) ? k21 : k20) * ((i & 1) ? c1 : c0), gelu2(bhi(v[i]), (i & 1) ? k11 : k10, (i & 1) ? k21 : k20) * ((i & 1) ? c1 : c0));
            stsm4(za + j * 2048, v[0], v[1], v[2], v[3]);
          }
          w_arrive(BAR(B_Z1S));
        }
        TSP(2, w == 0, 72 + wg);
      }
      if (STOP_AFTER >= 3) {
        if (!wg) {
          float g[112];
          uint32_t cp = 0;
          {
            const uint32_t bias[4] = {bs0, bs1, 0u, 0u};
            WG_FENCE();
            wrs96_first(g + 64, bias, mkdesc(sb + SM_ONE, 0, 0, 0)); wrs128_first(g, bias, mkdesc(sb + SM_ONE, 0, 0, 0));
            WG_COMMIT();
          }
#pragma unroll 1
          for (int rnd = 0;; rnd++) {
            const uint32_t sx = opaque(sb);
            const uint64_t dA2 = mkdesc(sx, 16, 1024, 1), dB2 = mkdesc(sx, 128, 1024, 0);
            const uint32_t fb = BAR(B_VAL), e0 = BAR(rnd ? B_EMPTY2 + 4 : B_NIL);
#pragma unroll
            for (int st = 0; st < 5; st++) {
              const uint64_t da = dA2 + (placeA(st) >> 4), db = dB2 + (placeB(st) >> 4);
              mbar_wait(fb + st * 8, rnd & 1);
              if (st == 0 || rnd == 0) TSP(4, w == 0, st ? 10 + st : 1 + rnd);
              WG_FENCE();
#pragma unroll
              for (int j = 0; j < 4; j++) { WSS<96, 0, 1>::mma(g + 64, da + j * 2, db + j * 16 + 1024); put(rnd == (st < 2), 1, 6 * st + j, bitsel(baffine(zb[6 * st + j], cp), par, tg)); }
#pragma unroll
              for (int j = 0; j < 4; j++) { WSS<128, 0, 1>::mma(g, da + j * 2, db + j * 16); if (j < 2 && st < 4) put(rnd == (st < 2), 1, 6 * st + 4 + j, bitsel(baffine(zb[6 * st + 4 + j], cp), par, tg)); }
              WG_COMMIT();
              WG_WAIT(1);
              if (lane == 0) mbar_arrive(st ? BAR(B_EMPTY2 + st - 1) : e0);
              if (st == 1) { if (rnd) goto g2_main; mbar_wait(BAR(B_CP), 0); cp = lds32(sb + SM_LNB + (t128 & ~3)); }
            }
          }
        g2_main:
          w_arrive(BAR(B_PUB));
          uint32_t z1[56];
#pragma unroll
          for (int i = 0; i < 56; i++) z1[i] = i < 28 ? zb[i] : ZINIT;
          const uint32_t zl = __shfl_sync(0xffffffffu, za, lane);
          uint32_t ph = 1;
          uint64_t dA2 = mkdesc(sb, 16, 1024, 1), dB2 = mkdesc(sb, 128, 1024, 0);
#pragma unroll 1
          for (int rnd = 1; rnd < 6; rnd++, ph ^= 1) {
            asm volatile("" : "+l"(dA2), "+l"(dB2));
#pragma unroll
            for (int k = 0; k < 5; k++) {
              const int st = (k + 2) % 5;
              const uint64_t da = dA2 + (placeA(st) >> 4), db = dB2 + (placeB(st) >> 4);
              if (k != 1) mbar_wait(BAR(B_VAL + st), k > 2 ? ph ^ 1 : ph); else mbar_wait2(BAR(B_VAL + st), BAR(rnd == 3 ? B_Z1S : B_CP), ph, 0);
              if (st == 0) TSP(4, w == 0, 2 + rnd); else TSP(4, w == 0, 95 + st);
              WG_FENCE();
#pragma unroll
              for (int j = 0; j < 4; j++) WSS<96, 0, 1>::mma(g + 64, da + j * 2, db + j * 16 + 1024);
#pragma unroll
              for (int j = 0; j < 4; j++) WSS<128, 0, 1>::mma(g, da + j * 2, db + j * 16);
              WG_COMMIT();
              WG_WAIT(1);
              if (lane == 0) mbar_arrive(BAR(B_EMPTY2 + (k + 1) % 5));
#pragma unroll
              for (int j = 0; j < 3; j++) if (5 * j + k) ldsm4_if(rnd == 3 + j, zl + (5 * j + k - 1) * 2048, z1 + 4 * (5 * j + k - 1));
            }
          }
          TSP(4, w == 0, 100);
          w_arrive_peer(BAR(B_PFREE) + peer);
          if (STOP_AFTER >= 4) bar_arrive(13, 256);
          WG_WAIT(0);
          if (lane == 0) mbar_arrive(BAR(B_EMPTY2 + 1));
          TSP(4, w == 0, 20);
          stage_end();
#pragma unroll
          for (int j = 0; j < 28; j += 2) {
#pragma unroll
            for (int i = 2 * j; i < 2 * j + 4; i++) z1[i] = bmul2(z1[i], pack2(g[2 * i], g[2 * i + 1]));
            stsm4(zl + j * 1024, z1[2 * j], z1[2 * j + 1], z1[2 * j + 2], z1[2 * j + 3]);
            if ((j == 12 && !PONE) || j == 26) { fence_async_s(); w_arrive(BAR(B_PST + (j >> 4))); TSP(4, w == 0, 21 + (j >> 4)); stage_end(); }
          }
        }
      }
      if (STOP_AFTER >= 4) {
        float o[64];
        undef<64>(o);
        mbar_wait(BAR(B_GB), 0);
#pragma unroll 1
        for (int it = 0; it <= wg; it++) {
          const int box = it ? 4 : (2 - 2 * wg) ^ (n & BOXX);
          uint4 gb[4];
#pragma unroll
          for (int i = 0; i < 4; i++) gb[i] = lds128(sb + SM_GB + box * 128 + i * 64 + q * 16);
#pragma unroll 1
          for (int t = 0; t < 2; t++) {
            const uint32_t sx = opaque(sb);
            const uint64_t da = mkdesc(sx + (t ? 0 : SM_PO), 1024, 128, 0);
            if (!(it & t)) bar_sync(12 + wg, 256);
            if (!it) {
              const uint32_t f0 = BAR(B_FULL2 + 4 - 2 * wg), f1 = BAR(B_FULL2 + 1 + 2 * wg), pb = BAR(t ? B_PP : B_PST);
#pragma unroll
              for (int j = 0; j < 2; j++) {
                const uint64_t db = mkdesc(sx + (wg ? placeB(2 + j) : placeB(4 - 3 * j)), 14336, 1024, 1);
                mbar_wait2(j ? f1 : f0, pb + (j || (PONE && !t)) * 8, t ^ (j & ~wg), 0);
                TSP(4, w == 0, 32 - 2 * wg + 4 * t + j);
                WG_FENCE();
#pragma unroll
                for (int i = 0; i < 7; i++) WSS<128, 0, 1>::mma(o, da + j * 896 + i * 128, db + i * 128, i || j || t);
                WG_COMMIT();
              }
              bar_arrive(13 - wg, 256);
              WG_WAIT(1);
              if (lane == 0) mbar_arrive(f0 + (B_EMPTY2 - B_FULL2) * 8);
              WG_WAIT(0);
              if (lane == 0) mbar_arrive(f1 + (B_EMPTY2 - B_FULL2) * 8);
            } else {
              const uint64_t db = mkdesc(sx + (t ? placeB(3) : placeB(2)), 0, 1024, 1);
              mbar_wait(BAR(B_FULL2 + 2 + t), 0);
              TSP(4, w == 0, 38 + t);
              WG_FENCE();
#pragma unroll
              for (int i = 0; i < 14; i++) WSS<64, 0, 1>::mma(o, da + i * 128, db + i * 128, i || t);
              WG_COMMIT();
            }
          }
          if (it == wg) w_arrive(BAR(B_DONE + wg));
          WG_WAIT(0);
          TSP(4, w == 0, 40 + it + 2 * !wg);
#pragma unroll
          for (int b = 0; b < 2; b++) {
            const uint32_t ob = sb + placeA(box + b) + w * 2048, oa = ob + (lane & 15) * 128 + (((mi >> 1) ^ rr) << 4);
#pragma unroll
            for (int i = 0; i < 4; i++) {
              const float* a = o + b * 32 + i * 8;
              const uint4 gq = gb[2 * b + (i >> 1)];
              const uint32_t g0 = (i & 1) ? gq.z : gq.x, g1 = (i & 1) ? gq.w : gq.y;
              stsm4(oa ^ (i * 32), bmul2(pack2(a[0], a[1]), g0), bmul2(pack2(a[2], a[3]), g0), bmul2(pack2(a[4], a[5]), g1), bmul2(pack2(a[6], a[7]), g1));
            }
            fence_async_s();
            __syncwarp();
            tma_rows_add(&tm.out, (box + b) * 128 + crank * 64, m & ~1, (m & 1) * 4 + w, ob);
            TSP(4, w == 0, 50 + box + b);
            if (it) break;
          }
        }
        bulk_commit();
        bulk_wait_read0();
        TSP(4, w == 0, 56 + wg);
        return;
      }
    }
  }
done:
  w_arrive(BAR(B_DONE + wg));
}

typedef CUresult (*EncodeFn)(CUtensorMap*, CUtensorMapDataType, cuuint32_t, void*, const cuuint64_t*, const cuuint64_t*, const cuuint32_t*, const cuuint32_t*,
                             CUtensorMapInterleave, CUtensorMapSwizzle, CUtensorMapL2promotion, CUtensorMapFloatOOBfill);
struct Dim { uint64_t size, stride; uint32_t box; };

CUtensorMap make_map(EncodeFn enc, const void* ptr, uint64_t cols, Dim a, Dim b = {0, 0, 0}, Dim c = {0, 0, 0}, Dim d = {0, 0, 0}, uint32_t width = 64) {
  CUtensorMap m;
  cuuint64_t gd[5] = {cols, a.size, b.size, c.size, d.size}, gs[4] = {a.stride, b.stride, c.stride, d.stride};
  cuuint32_t bd[5] = {width, a.box, b.box, c.box, d.box}, es[5] = {1, 1, 1, 1, 1};
  enc(&m, CU_TENSOR_MAP_DATA_TYPE_BFLOAT16, d.size ? 5 : c.size ? 4 : b.size ? 3 : 2, const_cast<void*>(ptr), gd, gs, bd, es, CU_TENSOR_MAP_INTERLEAVE_NONE,
      width == 64 ? CU_TENSOR_MAP_SWIZZLE_128B : width == 32 ? CU_TENSOR_MAP_SWIZZLE_64B : CU_TENSOR_MAP_SWIZZLE_NONE, CU_TENSOR_MAP_L2_PROMOTION_L2_128B, CU_TENSOR_MAP_FLOAT_OOB_FILL_NONE);
  return m;
}

}

extern "C" void kernel_launch(void* const* d_in, const int* in_sizes, int n_in, void* d_out, int out_size) {
  (void)in_sizes; (void)n_in; (void)out_size;
  void* fn = nullptr;
  cudaDriverEntryPointQueryResult qr;
  cudaGetDriverEntryPoint("cuTensorMapEncodeTiled", &fn, cudaEnableDefault, &qr);
  EncodeFn enc = (EncodeFn)fn;
  Params p;
  p.k = (const __nv_bfloat16*)d_in[1]; p.v = (const __nv_bfloat16*)d_in[2];
  p.shiftk = (const __nv_bfloat16*)d_in[3]; p.ssmk = (const __nv_bfloat16*)d_in[4]; p.ssmD = (const __nv_bfloat16*)d_in[5];
  p.bsp = (const __nv_bfloat16*)d_in[9]; p.c = (const __nv_bfloat16*)d_in[11]; p.wout = (const __nv_bfloat16*)d_in[10];
  p.wsp = (const __nv_bfloat16*)d_in[8];
  void* scr = nullptr;
  cudaGetSymbolAddress(&scr, g_scr);
  p.g = (Scratch*)scr;
  int dev = 0, nsm = 0;
  cudaGetDevice(&dev);
  cudaDeviceGetAttribute(&nsm, cudaDevAttrMultiProcessorCount, dev);
  p.by_sm = nsm == 132;
  for (int t = 0; t < 64; t++) {
    const int grp = t < 32 ? t & 7 : t < 60 ? (t - 32) % 7 + 1 : 0, i = t < 32 ? t >> 3 : t < 60 ? 4 + (t - 32) / 7 : t - 56;
    p.tile[t] = MAP44 ? grp * 8 + i : ((grp >> 1) * 8 + i) * 2 + (grp & 1);
  }
  const Dim one = {1, 16, 1};
  Maps tm;
  tm.k = make_map(enc, d_in[1], 640, {8, 1280, 10}, {256, 10240, 5}, one, one);
  tm.v = make_map(enc, d_in[2], 640, {8, 1280, 10}, {256, 10240, 4}, one, one);
  tm.f = make_map(enc, d_in[4], 256, {8, 512, 8}, {640, 4096, 1}, one, one, 256);
  tm.wm = make_map(enc, d_in[12], 3840, {640, 7680, 64}, one, one, one);
  tm.q = make_map(enc, d_in[0], 640, {2, 1280, 2}, {32, 81920, 2}, {8, 10240, 4}, {4, 2560, 4});
  tm.y = make_map(enc, p.g->Y, 32, {640, 4096, 64}, {64, 64, 2}, {0, 0, 0}, {0, 0, 0}, 32);
  tm.wm2 = make_map(enc, d_in[12], 64, {640, 7680, 64}, {60, 128, 2});
  tm.w3 = make_map(enc, d_in[7], 64, {640, 3456, 64}, {27, 128, 3});
  tm.wn = make_map(enc, d_in[7], 1728, {640, 3456, 64}, {0, 0, 0}, {0, 0, 0}, {0, 0, 0}, 32);
  tm.w2 = make_map(enc, d_in[7], 64, {640, 3456, 64}, {27, 128, 2});
  tm.wsp = make_map(enc, d_in[8], 2048, {8, 4096, 8}, {32, 262144, 2}, {8, 32768, MCAST ? 2u : 4u});
  tm.x1 = make_map(enc, d_out, 640, {2, 1280, 2}, {32, 81920, 2}, {8, 10240, 2}, {4, 2560, 4});
  tm.out = make_map(enc, d_out, 640, {8, 1280, 8}, {32, 81920, 2}, {8, 10240, 1});
  tm.wo = make_map(enc, d_in[10], 640, {864, 1280, 112});
  cudaFuncSetAttribute(fused_kernel, cudaFuncAttributeMaxDynamicSharedMemorySize, SM_TOTAL);
  cudaLaunchConfig_t cfg = {};
  cfg.gridDim = dim3(132); cfg.blockDim = dim3(512); cfg.dynamicSmemBytes = SM_TOTAL; cfg.stream = cudaStreamPerThread;
  cudaLaunchAttribute at[1];
  at[0].id = cudaLaunchAttributeCooperative; at[0].val.cooperative = 1;
  cfg.attrs = at; cfg.numAttrs = 1;
  cudaLaunchKernelEx(&cfg, fused_kernel, p, tm);
}
```

```cpp
#include <cuda_runtime.h>
#include <cuda.h>
#include <cuda_bf16.h>
#include <stdint.h>
#include <string.h>
#include <stddef.h>

#define SEQ0 0x1202211101201000ull
#define SEQ1 0x3130231404221303ull
#define SEQ2 0x4342414024343332ull
#define SEQ3 0x44ull
#define T_2 900
#define T_AB 1800
#define PACE_D 370
#define PACE_F 355
#define PACE_Q 355
#define PACE_W 555
#define T_WIN 13000
#define T_SPARE 11000
#define LOAD_AT 8
#define PUB_AT 16
#define WAIT1 600
#define GATE 1
#define HINT_A 2
#define CHAIN 1
#define PSTEP 4
#define POLL0 300
#define DELAY0 1700
#define POLL1 600
#define NAPA 700
#define NAPS 1
#define NAPM 500
#define HINT_M 1
#define H2 0
#define ZINIT 0
#define BOXX 2
#define XGAP 150
#define VT 1
#define RELJ 1
#define ROT 0
#define PONE 1
#define PGATE 3
#define STOP_AFTER 99

namespace {

template<int N> struct WRS;
template<int N, int TA, int TB> struct WSS;
template<> struct WRS<16> { static __device__ __forceinline__ void mma(float* d, const uint32_t* a, uint64_t db) {
  asm volatile("wgmma.mma_async.sync.aligned.m64n16k16.f32.bf16.bf16 {%0,%1,%2,%3,%4,%5,%6,%7}, {%8,%9,%10,%11}, %12, 1, 1, 1, 0;"
    : "+f"(d[0]),"+f"(d[1]),"+f"(d[2]),"+f"(d[3]),"+f"(d[4]),"+f"(d[5]),"+f"(d[6]),"+f"(d[7])
    : "r"(a[0]), "r"(a[1]), "r"(a[2]), "r"(a[3]), "l"(db)); } };
template<> struct WRS<32> { static __device__ __forceinline__ void mma(float* d, const uint32_t* a, uint64_t db) {
  asm volatile("wgmma.mma_async.sync.aligned.m64n32k16.f32.bf16.bf16 {%0,%1,%2,%3,%4,%5,%6,%7,%8,%9,%10,%11,%12,%13,%14,%15}, {%16,%17,%18,%19}, %20, 1, 1, 1, 0;"
    : "+f"(d[0]),"+f"(d[1]),"+f"(d[2]),"+f"(d[3]),"+f"(d[4]),"+f"(d[5]),"+f"(d[6]),"+f"(d[7]),"+f"(d[8]),"+f"(d[9]),"+f"(d[10]),"+f"(d[11]),"+f"(d[12]),"+f"(d[13]),"+f"(d[14]),"+f"(d[15])
    : "r"(a[0]), "r"(a[1]), "r"(a[2]), "r"(a[3]), "l"(db)); } };
template<> struct WRS<48> { static __device__ __forceinline__ void mma(float* d, const uint32_t* a, uint64_t db) {
  asm volatile("wgmma.mma_async.sync.aligned.m64n48k16.f32.bf16.bf16 {%0,%1,%2,%3,%4,%5,%6,%7,%8,%9,%10,%11,%12,%13,%14,%15,%16,%17,%18,%19,%20,%21,%22,%23}, {%24,%25,%26,%27}, %28, 1, 1, 1, 0;"
    : "+f"(d[0]),"+f"(d[1]),"+f"(d[2]),"+f"(d[3]),"+f"(d[4]),"+f"(d[5]),"+f"(d[6]),"+f"(d[7]),"+f"(d[8]),"+f"(d[9]),"+f"(d[10]),"+f"(d[11]),"+f"(d[12]),"+f"(d[13]),"+f"(d[14]),"+f"(d[15]),"+f"(d[16]),"+f"(d[17]),"+f"(d[18]),"+f"(d[19]),"+f"(d[20]),"+f"(d[21]),"+f"(d[22]),"+f"(d[23])
    : "r"(a[0]), "r"(a[1]), "r"(a[2]), "r"(a[3]), "l"(db)); } };
template<> struct WRS<64> { static __device__ __forceinline__ void mma(float* d, const uint32_t* a, uint64_t db) {
  asm volatile("wgmma.mma_async.sync.aligned.m64n64k16.f32.bf16.bf16 {%0,%1,%2,%3,%4,%5,%6,%7,%8,%9,%10,%11,%12,%13,%14,%15,%16,%17,%18,%19,%20,%21,%22,%23,%24,%25,%26,%27,%28,%29,%30,%31}, {%32,%33,%34,%35}, %36, 1, 1, 1, 0;"
    : "+f"(d[0]),"+f"(d[1]),"+f"(d[2]),"+f"(d[3]),"+f"(d[4]),"+f"(d[5]),"+f"(d[6]),"+f"(d[7]),"+f"(d[8]),"+f"(d[9]),"+f"(d[10]),"+f"(d[11]),"+f"(d[12]),"+f"(d[13]),"+f"(d[14]),"+f"(d[15]),"+f"(d[16]),"+f"(d[17]),"+f"(d[18]),"+f"(d[19]),"+f"(d[20]),"+f"(d[21]),"+f"(d[22]),"+f"(d[23]),"+f"(d[24]),"+f"(d[25]),"+f"(d[26]),"+f"(d[27]),"+f"(d[28]),"+f"(d[29]),"+f"(d[30]),"+f"(d[31])
    : "r"(a[0]), "r"(a[1]), "r"(a[2]), "r"(a[3]), "l"(db)); } };
template<> struct WRS<80> { static __device__ __forceinline__ void mma(float* d, const uint32_t* a, uint64_t db) {
  asm volatile("wgmma.mma_async.sync.aligned.m64n80k16.f32.bf16.bf16 {%0,%1,%2,%3,%4,%5,%6,%7,%8,%9,%10,%11,%12,%13,%14,%15,%16,%17,%18,%19,%20,%21,%22,%23,%24,%25,%26,%27,%28,%29,%30,%31,%32,%33,%34,%35,%36,%37,%38,%39}, {%40,%41,%42,%43}, %44, 1, 1, 1, 0;"
    : "+f"(d[0]),"+f"(d[1]),"+f"(d[2]),"+f"(d[3]),"+f"(d[4]),"+f"(d[5]),"+f"(d[6]),"+f"(d[7]),"+f"(d[8]),"+f"(d[9]),"+f"(d[10]),"+f"(d[11]),"+f"(d[12]),"+f"(d[13]),"+f"(d[14]),"+f"(d[15]),"+f"(d[16]),"+f"(d[17]),"+f"(d[18]),"+f"(d[19]),"+f"(d[20]),"+f"(d[21]),"+f"(d[22]),"+f"(d[23]),"+f"(d[24]),"+f"(d[25]),"+f"(d[26]),"+f"(d[27]),"+f"(d[28]),"+f"(d[29]),"+f"(d[30]),"+f"(d[31]),"+f"(d[32]),"+f"(d[33]),"+f"(d[34]),"+f"(d[35]),"+f"(d[36]),"+f"(d[37]),"+f"(d[38]),"+f"(d[39])
    : "r"(a[0]), "r"(a[1]), "r"(a[2]), "r"(a[3]), "l"(db)); } };
template<> struct WRS<96> { static __device__ __forceinline__ void mma(float* d, const uint32_t* a, uint64_t db) {
  asm volatile("wgmma.mma_async.sync.aligned.m64n96k16.f32.bf16.bf16 {%0,%1,%2,%3,%4,%5,%6,%7,%8,%9,%10,%11,%12,%13,%14,%15,%16,%17,%18,%19,%20,%21,%22,%23,%24,%25,%26,%27,%28,%29,%30,%31,%32,%33,%34,%35,%36,%37,%38,%39,%40,%41,%42,%43,%44,%45,%46,%47}, {%48,%49,%50,%51}, %52, 1, 1, 1, 0;"
    : "+f"(d[0]),"+f"(d[1]),"+f"(d[2]),"+f"(d[3]),"+f"(d[4]),"+f"(d[5]),"+f"(d[6]),"+f"(d[7]),"+f"(d[8]),"+f"(d[9]),"+f"(d[10]),"+f"(d[11]),"+f"(d[12]),"+f"(d[13]),"+f"(d[14]),"+f"(d[15]),"+f"(d[16]),"+f"(d[17]),"+f"(d[18]),"+f"(d[19]),"+f"(d[20]),"+f"(d[21]),"+f"(d[22]),"+f"(d[23]),"+f"(d[24]),"+f"(d[25]),"+f"(d[26]),"+f"(d[27]),"+f"(d[28]),"+f"(d[29]),"+f"(d[30]),"+f"(d[31]),"+f"(d[32]),"+f"(d[33]),"+f"(d[34]),"+f"(d[35]),"+f"(d[36]),"+f"(d[37]),"+f"(d[38]),"+f"(d[39]),"+f"(d[40]),"+f"(d[41]),"+f"(d[42]),"+f"(d[43]),"+f"(d[44]),"+f"(d[45]),"+f"(d[46]),"+f"(d[47])
    : "r"(a[0]), "r"(a[1]), "r"(a[2]), "r"(a[3]), "l"(db)); } };
template<> struct WRS<112> { static __device__ __forceinline__ void mma(float* d, const uint32_t* a, uint64_t db) {
  asm volatile("wgmma.mma_async.sync.aligned.m64n112k16.f32.bf16.bf16 {%0,%1,%2,%3,%4,%5,%6,%7,%8,%9,%10,%11,%12,%13,%14,%15,%16,%17,%18,%19,%20,%21,%22,%23,%24,%25,%26,%27,%28,%29,%30,%31,%32,%33,%34,%35,%36,%37,%38,%39,%40,%41,%42,%43,%44,%45,%46,%47,%48,%49,%50,%51,%52,%53,%54,%55}, {%56,%57,%58,%59}, %60, 1, 1, 1, 0;"
    : "+f"(d[0]),"+f"(d[1]),"+f"(d[2]),"+f"(d[3]),"+f"(d[4]),"+f"(d[5]),"+f"(d[6]),"+f"(d[7]),"+f"(d[8]),"+f"(d[9]),"+f"(d[10]),"+f"(d[11]),"+f"(d[12]),"+f"(d[13]),"+f"(d[14]),"+f"(d[15]),"+f"(d[16]),"+f"(d[17]),"+f"(d[18]),"+f"(d[19]),"+f"(d[20]),"+f"(d[21]),"+f"(d[22]),"+f"(d[23]),"+f"(d[24]),"+f"(d[25]),"+f"(d[26]),"+f"(d[27]),"+f"(d[28]),"+f"(d[29]),"+f"(d[30]),"+f"(d[31]),"+f"(d[32]),"+f"(d[33]),"+f"(d[34]),"+f"(d[35]),"+f"(d[36]),"+f"(d[37]),"+f"(d[38]),"+f"(d[39]),"+f"(d[40]),"+f"(d[41]),"+f"(d[42]),"+f"(d[43]),"+f"(d[44]),"+f"(d[45]),"+f"(d[46]),"+f"(d[47]),"+f"(d[48]),"+f"(d[49]),"+f"(d[50]),"+f"(d[51]),"+f"(d[52]),"+f"(d[53]),"+f"(d[54]),"+f"(d[55])
    : "r"(a[0]), "r"(a[1]), "r"(a[2]), "r"(a[3]), "l"(db)); } };
template<> struct WRS<128> { static __device__ __forceinline__ void mma(float* d, const uint32_t* a, uint64_t db) {
  asm volatile("wgmma.mma_async.sync.aligned.m64n128k16.f32.bf16.bf16 {%0,%1,%2,%3,%4,%5,%6,%7,%8,%9,%10,%11,%12,%13,%14,%15,%16,%17,%18,%19,%20,%21,%22,%23,%24,%25,%26,%27,%28,%29,%30,%31,%32,%33,%34,%35,%36,%37,%38,%39,%40,%41,%42,%43,%44,%45,%46,%47,%48,%49,%50,%51,%52,%53,%54,%55,%56,%57,%58,%59,%60,%61,%62,%63}, {%64,%65,%66,%67}, %68, 1, 1, 1, 0;"
    : "+f"(d[0]),"+f"(d[1]),"+f"(d[2]),"+f"(d[3]),"+f"(d[4]),"+f"(d[5]),"+f"(d[6]),"+f"(d[7]),"+f"(d[8]),"+f"(d[9]),"+f"(d[10]),"+f"(d[11]),"+f"(d[12]),"+f"(d[13]),"+f"(d[14]),"+f"(d[15]),"+f"(d[16]),"+f"(d[17]),"+f"(d[18]),"+f"(d[19]),"+f"(d[20]),"+f"(d[21]),"+f"(d[22]),"+f"(d[23]),"+f"(d[24]),"+f"(d[25]),"+f"(d[26]),"+f"(d[27]),"+f"(d[28]),"+f"(d[29]),"+f"(d[30]),"+f"(d[31]),"+f"(d[32]),"+f"(d[33]),"+f"(d[34]),"+f"(d[35]),"+f"(d[36]),"+f"(d[37]),"+f"(d[38]),"+f"(d[39]),"+f"(d[40]),"+f"(d[41]),"+f"(d[42]),"+f"(d[43]),"+f"(d[44]),"+f"(d[45]),"+f"(d[46]),"+f"(d[47]),"+f"(d[48]),"+f"(d[49]),"+f"(d[50]),"+f"(d[51]),"+f"(d[52]),"+f"(d[53]),"+f"(d[54]),"+f"(d[55]),"+f"(d[56]),"+f"(d[57]),"+f"(d[58]),"+f"(d[59]),"+f"(d[60]),"+f"(d[61]),"+f"(d[62]),"+f"(d[63])
    : "r"(a[0]), "r"(a[1]), "r"(a[2]), "r"(a[3]), "l"(db)); } };
template<> struct WRS<192> { static __device__ __forceinline__ void mma(float* d, const uint32_t* a, uint64_t db) {
  asm volatile("wgmma.mma_async.sync.aligned.m64n192k16.f32.bf16.bf16 {%0,%1,%2,%3,%4,%5,%6,%7,%8,%9,%10,%11,%12,%13,%14,%15,%16,%17,%18,%19,%20,%21,%22,%23,%24,%25,%26,%27,%28,%29,%30,%31,%32,%33,%34,%35,%36,%37,%38,%39,%40,%41,%42,%43,%44,%45,%46,%47,%48,%49,%50,%51,%52,%53,%54,%55,%56,%57,%58,%59,%60,%61,%62,%63,%64,%65,%66,%67,%68,%69,%70,%71,%72,%73,%74,%75,%76,%77,%78,%79,%80,%81,%82,%83,%84,%85,%86,%87,%88,%89,%90,%91,%92,%93,%94,%95}, {%96,%97,%98,%99}, %100, 1, 1, 1, 0;"
    : "+f"(d[0]),"+f"(d[1]),"+f"(d[2]),"+f"(d[3]),"+f"(d[4]),"+f"(d[5]),"+f"(d[6]),"+f"(d[7]),"+f"(d[8]),"+f"(d[9]),"+f"(d[10]),"+f"(d[11]),"+f"(d[12]),"+f"(d[13]),"+f"(d[14]),"+f"(d[15]),"+f"(d[16]),"+f"(d[17]),"+f"(d[18]),"+f"(d[19]),"+f"(d[20]),"+f"(d[21]),"+f"(d[22]),"+f"(d[23]),"+f"(d[24]),"+f"(d[25]),"+f"(d[26]),"+f"(d[27]),"+f"(d[28]),"+f"(d[29]),"+f"(d[30]),"+f"(d[31]),"+f"(d[32]),"+f"(d[33]),"+f"(d[34]),"+f"(d[35]),"+f"(d[36]),"+f"(d[37]),"+f"(d[38]),"+f"(d[39]),"+f"(d[40]),"+f"(d[41]),"+f"(d[42]),"+f"(d[43]),"+f"(d[44]),"+f"(d[45]),"+f"(d[46]),"+f"(d[47]),"+f"(d[48]),"+f"(d[49]),"+f"(d[50]),"+f"(d[51]),"+f"(d[52]),"+f"(d[53]),"+f"(d[54]),"+f"(d[55]),"+f"(d[56]),"+f"(d[57]),"+f"(d[58]),"+f"(d[59]),"+f"(d[60]),"+f"(d[61]),"+f"(d[62]),"+f"(d[63]),"+f"(d[64]),"+f"(d[65]),"+f"(d[66]),"+f"(d[67]),"+f"(d[68]),"+f"(d[69]),"+f"(d[70]),"+f"(d[71]),"+f"(d[72]),"+f"(d[73]),"+f"(d[74]),"+f"(d[75]),"+f"(d[76]),"+f"(d[77]),"+f"(d[78]),"+f"(d[79]),"+f"(d[80]),"+f"(d[81]),"+f"(d[82]),"+f"(d[83]),"+f"(d[84]),"+f"(d[85]),"+f"(d[86]),"+f"(d[87]),"+f"(d[88]),"+f"(d[89]),"+f"(d[90]),"+f"(d[91]),"+f"(d[92]),"+f"(d[93]),"+f"(d[94]),"+f"(d[95])
    : "r"(a[0]), "r"(a[1]), "r"(a[2]), "r"(a[3]), "l"(db)); } };
template<> struct WSS<192,1,1> { static __device__ __forceinline__ void mma(float* d, uint64_t da, uint64_t db, int acc = 1) {
  asm volatile("{\n.reg .pred p;\nsetp.ne.b32 p, %98, 0;\nwgmma.mma_async.sync.aligned.m64n192k16.f32.bf16.bf16 {%0,%1,%2,%3,%4,%5,%6,%7,%8,%9,%10,%11,%12,%13,%14,%15,%16,%17,%18,%19,%20,%21,%22,%23,%24,%25,%26,%27,%28,%29,%30,%31,%32,%33,%34,%35,%36,%37,%38,%39,%40,%41,%42,%43,%44,%45,%46,%47,%48,%49,%50,%51,%52,%53,%54,%55,%56,%57,%58,%59,%60,%61,%62,%63,%64,%65,%66,%67,%68,%69,%70,%71,%72,%73,%74,%75,%76,%77,%78,%79,%80,%81,%82,%83,%84,%85,%86,%87,%88,%89,%90,%91,%92,%93,%94,%95}, %96, %97, p, 1, 1, 1, 1;\n}"
    : "+f"(d[0]),"+f"(d[1]),"+f"(d[2]),"+f"(d[3]),"+f"(d[4]),"+f"(d[5]),"+f"(d[6]),"+f"(d[7]),"+f"(d[8]),"+f"(d[9]),"+f"(d[10]),"+f"(d[11]),"+f"(d[12]),"+f"(d[13]),"+f"(d[14]),"+f"(d[15]),"+f"(d[16]),"+f"(d[17]),"+f"(d[18]),"+f"(d[19]),"+f"(d[20]),"+f"(d[21]),"+f"(d[22]),"+f"(d[23]),"+f"(d[24]),"+f"(d[25]),"+f"(d[26]),"+f"(d[27]),"+f"(d[28]),"+f"(d[29]),"+f"(d[30]),"+f"(d[31]),"+f"(d[32]),"+f"(d[33]),"+f"(d[34]),"+f"(d[35]),"+f"(d[36]),"+f"(d[37]),"+f"(d[38]),"+f"(d[39]),"+f"(d[40]),"+f"(d[41]),"+f"(d[42]),"+f"(d[43]),"+f"(d[44]),"+f"(d[45]),"+f"(d[46]),"+f"(d[47]),"+f"(d[48]),"+f"(d[49]),"+f"(d[50]),"+f"(d[51]),"+f"(d[52]),"+f"(d[53]),"+f"(d[54]),"+f"(d[55]),"+f"(d[56]),"+f"(d[57]),"+f"(d[58]),"+f"(d[59]),"+f"(d[60]),"+f"(d[61]),"+f"(d[62]),"+f"(d[63]),"+f"(d[64]),"+f"(d[65]),"+f"(d[66]),"+f"(d[67]),"+f"(d[68]),"+f"(d[69]),"+f"(d[70]),"+f"(d[71]),"+f"(d[72]),"+f"(d[73]),"+f"(d[74]),"+f"(d[75]),"+f"(d[76]),"+f"(d[77]),"+f"(d[78]),"+f"(d[79]),"+f"(d[80]),"+f"(d[81]),"+f"(d[82]),"+f"(d[83]),"+f"(d[84]),"+f"(d[85]),"+f"(d[86]),"+f"(d[87]),"+f"(d[88]),"+f"(d[89]),"+f"(d[90]),"+f"(d[91]),"+f"(d[92]),"+f"(d[93]),"+f"(d[94]),"+f"(d[95])
    : "l"(da), "l"(db), "r"(acc)); } };
template<> struct WSS<32,1,1> { static __device__ __forceinline__ void mma(float* d, uint64_t da, uint64_t db, int acc = 1) {
  asm volatile("{\n.reg .pred p;\nsetp.ne.b32 p, %18, 0;\nwgmma.mma_async.sync.aligned.m64n32k16.f32.bf16.bf16 {%0,%1,%2,%3,%4,%5,%6,%7,%8,%9,%10,%11,%12,%13,%14,%15}, %16, %17, p, 1, 1, 1, 1;\n}"
    : "+f"(d[0]),"+f"(d[1]),"+f"(d[2]),"+f"(d[3]),"+f"(d[4]),"+f"(d[5]),"+f"(d[6]),"+f"(d[7]),"+f"(d[8]),"+f"(d[9]),"+f"(d[10]),"+f"(d[11]),"+f"(d[12]),"+f"(d[13]),"+f"(d[14]),"+f"(d[15])
    : "l"(da), "l"(db), "r"(acc)); } };
template<> struct WSS<128,0,1> { static __device__ __forceinline__ void mma(float* d, uint64_t da, uint64_t db, int acc = 1) {
  asm volatile("{\n.reg .pred p;\nsetp.ne.b32 p, %66, 0;\nwgmma.mma_async.sync.aligned.m64n128k16.f32.bf16.bf16 {%0,%1,%2,%3,%4,%5,%6,%7,%8,%9,%10,%11,%12,%13,%14,%15,%16,%17,%18,%19,%20,%21,%22,%23,%24,%25,%26,%27,%28,%29,%30,%31,%32,%33,%34,%35,%36,%37,%38,%39,%40,%41,%42,%43,%44,%45,%46,%47,%48,%49,%50,%51,%52,%53,%54,%55,%56,%57,%58,%59,%60,%61,%62,%63}, %64, %65, p, 1, 1, 0, 1;\n}"
    : "+f"(d[0]),"+f"(d[1]),"+f"(d[2]),"+f"(d[3]),"+f"(d[4]),"+f"(d[5]),"+f"(d[6]),"+f"(d[7]),"+f"(d[8]),"+f"(d[9]),"+f"(d[10]),"+f"(d[11]),"+f"(d[12]),"+f"(d[13]),"+f"(d[14]),"+f"(d[15]),"+f"(d[16]),"+f"(d[17]),"+f"(d[18]),"+f"(d[19]),"+f"(d[20]),"+f"(d[21]),"+f"(d[22]),"+f"(d[23]),"+f"(d[24]),"+f"(d[25]),"+f"(d[26]),"+f"(d[27]),"+f"(d[28]),"+f"(d[29]),"+f"(d[30]),"+f"(d[31]),"+f"(d[32]),"+f"(d[33]),"+f"(d[34]),"+f"(d[35]),"+f"(d[36]),"+f"(d[37]),"+f"(d[38]),"+f"(d[39]),"+f"(d[40]),"+f"(d[41]),"+f"(d[42]),"+f"(d[43]),"+f"(d[44]),"+f"(d[45]),"+f"(d[46]),"+f"(d[47]),"+f"(d[48]),"+f"(d[49]),"+f"(d[50]),"+f"(d[51]),"+f"(d[52]),"+f"(d[53]),"+f"(d[54]),"+f"(d[55]),"+f"(d[56]),"+f"(d[57]),"+f"(d[58]),"+f"(d[59]),"+f"(d[60]),"+f"(d[61]),"+f"(d[62]),"+f"(d[63])
    : "l"(da), "l"(db), "r"(acc)); } };
template<> struct WSS<96,0,1> { static __device__ __forceinline__ void mma(float* d, uint64_t da, uint64_t db, int acc = 1) {
  asm volatile("{\n.reg .pred p;\nsetp.ne.b32 p, %50, 0;\nwgmma.mma_async.sync.aligned.m64n96k16.f32.bf16.bf16 {%0,%1,%2,%3,%4,%5,%6,%7,%8,%9,%10,%11,%12,%13,%14,%15,%16,%17,%18,%19,%20,%21,%22,%23,%24,%25,%26,%27,%28,%29,%30,%31,%32,%33,%34,%35,%36,%37,%38,%39,%40,%41,%42,%43,%44,%45,%46,%47}, %48, %49, p, 1, 1, 0, 1;\n}"
    : "+f"(d[0]),"+f"(d[1]),"+f"(d[2]),"+f"(d[3]),"+f"(d[4]),"+f"(d[5]),"+f"(d[6]),"+f"(d[7]),"+f"(d[8]),"+f"(d[9]),"+f"(d[10]),"+f"(d[11]),"+f"(d[12]),"+f"(d[13]),"+f"(d[14]),"+f"(d[15]),"+f"(d[16]),"+f"(d[17]),"+f"(d[18]),"+f"(d[19]),"+f"(d[20]),"+f"(d[21]),"+f"(d[22]),"+f"(d[23]),"+f"(d[24]),"+f"(d[25]),"+f"(d[26]),"+f"(d[27]),"+f"(d[28]),"+f"(d[29]),"+f"(d[30]),"+f"(d[31]),"+f"(d[32]),"+f"(d[33]),"+f"(d[34]),"+f"(d[35]),"+f"(d[36]),"+f"(d[37]),"+f"(d[38]),"+f"(d[39]),"+f"(d[40]),"+f"(d[41]),"+f"(d[42]),"+f"(d[43]),"+f"(d[44]),"+f"(d[45]),"+f"(d[46]),"+f"(d[47])
    : "l"(da), "l"(db), "r"(acc)); } };
template<> struct WSS<64,0,1> { static __device__ __forceinline__ void mma(float* d, uint64_t da, uint64_t db, int acc = 1) {
  asm volatile("{\n.reg .pred p;\nsetp.ne.b32 p, %34, 0;\nwgmma.mma_async.sync.aligned.m64n64k16.f32.bf16.bf16 {%0,%1,%2,%3,%4,%5,%6,%7,%8,%9,%10,%11,%12,%13,%14,%15,%16,%17,%18,%19,%20,%21,%22,%23,%24,%25,%26,%27,%28,%29,%30,%31}, %32, %33, p, 1, 1, 0, 1;\n}"
    : "+f"(d[0]),"+f"(d[1]),"+f"(d[2]),"+f"(d[3]),"+f"(d[4]),"+f"(d[5]),"+f"(d[6]),"+f"(d[7]),"+f"(d[8]),"+f"(d[9]),"+f"(d[10]),"+f"(d[11]),"+f"(d[12]),"+f"(d[13]),"+f"(d[14]),"+f"(d[15]),"+f"(d[16]),"+f"(d[17]),"+f"(d[18]),"+f"(d[19]),"+f"(d[20]),"+f"(d[21]),"+f"(d[22]),"+f"(d[23]),"+f"(d[24]),"+f"(d[25]),"+f"(d[26]),"+f"(d[27]),"+f"(d[28]),"+f"(d[29]),"+f"(d[30]),"+f"(d[31])
    : "l"(da), "l"(db), "r"(acc)); } };
template<> struct WSS<8,1,0> { static __device__ __forceinline__ void mma(float* d, uint64_t da, uint64_t db, int acc = 1) {
  asm volatile("{\n.reg .pred p;\nsetp.ne.b32 p, %6, 0;\nwgmma.mma_async.sync.aligned.m64n8k16.f32.bf16.bf16 {%0,%1,%2,%3}, %4, %5, p, 1, 1, 1, 0;\n}"
    : "+f"(d[0]),"+f"(d[1]),"+f"(d[2]),"+f"(d[3])
    : "l"(da), "l"(db), "r"(acc)); } };
__device__ __forceinline__ void wrs128_first(float* d, const uint32_t* a, uint64_t db) {
  asm volatile("wgmma.mma_async.sync.aligned.m64n128k16.f32.bf16.bf16 {%0,%1,%2,%3,%4,%5,%6,%7,%8,%9,%10,%11,%12,%13,%14,%15,%16,%17,%18,%19,%20,%21,%22,%23,%24,%25,%26,%27,%28,%29,%30,%31,%32,%33,%34,%35,%36,%37,%38,%39,%40,%41,%42,%43,%44,%45,%46,%47,%48,%49,%50,%51,%52,%53,%54,%55,%56,%57,%58,%59,%60,%61,%62,%63}, {%64,%65,%66,%67}, %68, 0, 1, 1, 0;"
    : "=f"(d[0]),"=f"(d[1]),"=f"(d[2]),"=f"(d[3]),"=f"(d[4]),"=f"(d[5]),"=f"(d[6]),"=f"(d[7]),"=f"(d[8]),"=f"(d[9]),"=f"(d[10]),"=f"(d[11]),"=f"(d[12]),"=f"(d[13]),"=f"(d[14]),"=f"(d[15]),"=f"(d[16]),"=f"(d[17]),"=f"(d[18]),"=f"(d[19]),"=f"(d[20]),"=f"(d[21]),"=f"(d[22]),"=f"(d[23]),"=f"(d[24]),"=f"(d[25]),"=f"(d[26]),"=f"(d[27]),"=f"(d[28]),"=f"(d[29]),"=f"(d[30]),"=f"(d[31]),"=f"(d[32]),"=f"(d[33]),"=f"(d[34]),"=f"(d[35]),"=f"(d[36]),"=f"(d[37]),"=f"(d[38]),"=f"(d[39]),"=f"(d[40]),"=f"(d[41]),"=f"(d[42]),"=f"(d[43]),"=f"(d[44]),"=f"(d[45]),"=f"(d[46]),"=f"(d[47]),"=f"(d[48]),"=f"(d[49]),"=f"(d[50]),"=f"(d[51]),"=f"(d[52]),"=f"(d[53]),"=f"(d[54]),"=f"(d[55]),"=f"(d[56]),"=f"(d[57]),"=f"(d[58]),"=f"(d[59]),"=f"(d[60]),"=f"(d[61]),"=f"(d[62]),"=f"(d[63])
    : "r"(a[0]), "r"(a[1]), "r"(a[2]), "r"(a[3]), "l"(db)); }
__device__ __forceinline__ void wrs96_first(float* d, const uint32_t* a, uint64_t db) {
  asm volatile("wgmma.mma_async.sync.aligned.m64n96k16.f32.bf16.bf16 {%0,%1,%2,%3,%4,%5,%6,%7,%8,%9,%10,%11,%12,%13,%14,%15,%16,%17,%18,%19,%20,%21,%22,%23,%24,%25,%26,%27,%28,%29,%30,%31,%32,%33,%34,%35,%36,%37,%38,%39,%40,%41,%42,%43,%44,%45,%46,%47}, {%48,%49,%50,%51}, %52, 0, 1, 1, 0;"
    : "=f"(d[0]),"=f"(d[1]),"=f"(d[2]),"=f"(d[3]),"=f"(d[4]),"=f"(d[5]),"=f"(d[6]),"=f"(d[7]),"=f"(d[8]),"=f"(d[9]),"=f"(d[10]),"=f"(d[11]),"=f"(d[12]),"=f"(d[13]),"=f"(d[14]),"=f"(d[15]),"=f"(d[16]),"=f"(d[17]),"=f"(d[18]),"=f"(d[19]),"=f"(d[20]),"=f"(d[21]),"=f"(d[22]),"=f"(d[23]),"=f"(d[24]),"=f"(d[25]),"=f"(d[26]),"=f"(d[27]),"=f"(d[28]),"=f"(d[29]),"=f"(d[30]),"=f"(d[31]),"=f"(d[32]),"=f"(d[33]),"=f"(d[34]),"=f"(d[35]),"=f"(d[36]),"=f"(d[37]),"=f"(d[38]),"=f"(d[39]),"=f"(d[40]),"=f"(d[41]),"=f"(d[42]),"=f"(d[43]),"=f"(d[44]),"=f"(d[45]),"=f"(d[46]),"=f"(d[47])
    : "r"(a[0]), "r"(a[1]), "r"(a[2]), "r"(a[3]), "l"(db)); }

constexpr int IMG = 1792;
struct Scratch {
  unsigned cnt[32 * 32];
  float modp[2 * 3200];
  float gb[640];
  uint4 vt[8 * 224];
  uint2 st3[128 * 64];
  uint4 T[640 * 256];
  uint4 Y[640 * 256];
  uint4 z2n[4 * 32 * IMG];
};
__device__ __align__(1024) Scratch g_scr;
enum { C_A = 0, C_Y = 10, C_M = 20, C_G = 22, C_H = 24  , C_E = 28 };

constexpr uint32_t SM_R = 81920, SM_PO = 184320, SM_S = 212992, SM_X1 = 221184, SM_TAIL = 229376, SM_TOTAL = 232448;
constexpr uint32_t KV_V = 7168;
constexpr uint32_t SM_VT = SM_S, SM_LN1 = SM_S, SM_MOD = SM_S + 3584, SM_LN2 = SM_S + 6144, SM_SILU = SM_LN2;
constexpr uint32_t SM_BAR = SM_TAIL, SM_TPC = SM_BAR + 912, SM_DUMMY = SM_TPC + 48, SM_LNB = SM_DUMMY + 64, SM_PROF = SM_LNB + 1024, SM_ONE = SM_PROF + 512, SM_GB = SM_MOD;
static_assert(SM_ONE + 128 <= SM_TOTAL, "smem");
__device__ __forceinline__ uint32_t offU(int s) { return SM_R + ((0x64302u >> (4 * s)) & 15) * 16384; }
__device__ __forceinline__ uint32_t offX(int s) { return s < 2 ? SM_X1 + s * 4096 : SM_R - 36864 + s * 32768; }
__device__ __forceinline__ uint32_t offF(int s) { return offU(s) + 4208; }
__host__ __device__ constexpr uint32_t placeB(int st) { return ((uint32_t)(0x9874245000ull >> (8 * st)) & 255) * 1024; }
__host__ __device__ constexpr uint32_t placeA(int st) { return ((uint32_t)(0x40906C1CD8ull >> (8 * st)) & 255) * 1024; }
__device__ __forceinline__ int nstart(int n) { return n < 3 ? 224 * n : 640; }
enum {
  B_KV = 0, B_F = 5, B_WM = 10, B_Q = 15, B_U = 20, B_YH = 25  , B_AP = 31, B_LN = 36  , B_PP = 38  ,
  B_G0 = 41, B_VT = 42, B_X1D = 45, B_CP = 46, B_ACK = 43, B_GB = 44, B_LOK = 47  ,
  B_FULL1 = 50, B_FULL2 = 54,
  B_KVF = 64, B_EMPTY1 = 69, B_EMPTY2 = 73, B_VAL = 78, B_PST = 83  , B_VTF = 85, B_PUB = 86, B_Z1S = 87, B_PFREE = 88, B_NIL = 89,
  B_DONE = 90  , B_AO = 94, B_LNB = 99, B_RF = 100, B_MT = 105, B_WMF = 106, B_FO = 107, B_G1 = 112
};

struct Params {
  const __nv_bfloat16 *k, *v, *c;
  Scratch* g;
  const __nv_bfloat16* shiftk;
  int by_sm;
  const __nv_bfloat16 *ssmD, *bsp, *wout, *wsp;
  uint8_t tile[64];
};

struct Maps { CUtensorMap k, v, f, wm, q, y, w2, x1, wsp, out, wo, wm2, w3, wn; };

__device__ __forceinline__ void mbar_arrive(uint32_t a) { asm volatile("mbarrier.arrive.shared::cta.b64 _, [%0];" ::"r"(a) : "memory"); }
__device__ __forceinline__ void mbar_expect(uint32_t a, int b) { asm volatile("mbarrier.arrive.expect_tx.shared::cta.b64 _, [%0], %1;" ::"r"(a), "r"(b) : "memory"); }
__device__ __forceinline__ void mbar_wait(uint32_t a, int ph) {
  asm volatile("{\n.reg .pred p;\nWL:\nmbarrier.try_wait.parity.shared::cta.b64 p, [%0], %1;\n@!p bra WL;\n}" ::"r"(a), "r"(ph) : "memory");
}
__device__ __forceinline__ void mbar_wait2(uint32_t a, uint32_t b, int pa, int pb) {
  asm volatile("{\n.reg .pred p, q;\nWL:\nmbarrier.try_wait.parity.shared::cta.b64 p, [%0], %2;\nmbarrier.try_wait.parity.shared::cta.b64 q, [%1], %3;\nand.pred p, p, q;\n@!p bra WL;\n}" ::"r"(a), "r"(b), "r"(pa), "r"(pb) : "memory");
}
__device__ __forceinline__ uint32_t mbar_test(uint32_t a, int ph) {
  uint32_t r;
  asm volatile("{\n.reg .pred p;\nmbarrier.test_wait.parity.shared::cta.b64 p, [%1], %2;\nselp.u32 %0, 1, 0, p;\n}" : "=r"(r) : "r"(a), "r"(ph) : "memory");
  return r;
}
__device__ __forceinline__ void mbar_wait_b(uint32_t a, int ph) {
  asm volatile("{\n.reg .pred p;\n.reg .u32 c;\nmov.u32 c, 0;\nWL:\nmbarrier.try_wait.parity.shared::cta.b64 p, [%0], %1;\n@p bra WD;\n"
               "add.u32 c, c, 1;\nsetp.lt.u32 p, c, 0x10000;\n@p bra WL;\ntrap;\nWD:\n}" ::"r"(a), "r"(ph) : "memory");
}
__device__ __forceinline__ uint32_t mapa(uint32_t a, uint32_t rank) { uint32_t r; asm("mapa.shared::cluster.u32 %0, %1, %2;" : "=r"(r) : "r"(a), "r"(rank)); return r; }
__device__ __forceinline__ void bar_sync(int id, int n) { asm volatile("bar.sync %0, %1;" ::"r"(id), "r"(n) : "memory"); }
__device__ __forceinline__ void bar_arrive(int id, int n) { asm volatile("bar.arrive %0, %1;" ::"r"(id), "r"(n) : "memory"); }
__device__ __forceinline__ unsigned ld_acquire(const void* p) { unsigned v; asm volatile("ld.acquire.gpu.global.u32 %0, [%1];" : "=r"(v) : "l"(p) : "memory"); return v; }
__device__ __forceinline__ unsigned ld_relaxed(const void* p) { unsigned v; asm volatile("ld.relaxed.gpu.global.u32 %0, [%1];" : "=r"(v) : "l"(p) : "memory"); return v; }
__device__ __forceinline__ uint4 ld_relaxed4(const void* p) { uint4 v; asm volatile("ld.relaxed.gpu.global.v4.u32 {%0,%1,%2,%3}, [%4];" : "=r"(v.x), "=r"(v.y), "=r"(v.z), "=r"(v.w) : "l"(p) : "memory"); return v; }
__device__ __forceinline__ void st_relaxed4(void* p, uint4 v) { asm volatile("st.relaxed.gpu.global.v4.u32 [%0], {%1,%2,%3,%4};" ::"l"(p), "r"(v.x), "r"(v.y), "r"(v.z), "r"(v.w) : "memory"); }
__device__ __forceinline__ uint2 ld_relaxed2(const void* p) { uint2 v; asm volatile("ld.relaxed.gpu.global.v2.u32 {%0,%1}, [%2];" : "=r"(v.x), "=r"(v.y) : "l"(p) : "memory"); return v; }
__device__ __forceinline__ void st_relaxed2(void* p, uint32_t a, uint32_t b) { asm volatile("st.relaxed.gpu.global.v2.u32 [%0], {%1,%2};" ::"l"(p), "r"(a), "r"(b) : "memory"); }
__device__ __forceinline__ void st_relaxed(void* p, unsigned v) { asm volatile("st.relaxed.gpu.global.u32 [%0], %1;" ::"l"(p), "r"(v) : "memory"); }
__device__ __forceinline__ void fence_gpu() { asm volatile("fence.acq_rel.gpu;" ::: "memory"); }
__device__ __forceinline__ void wait_cnt(const unsigned* c, unsigned target) {
#pragma unroll 1
  while (__any_sync(0xffffffffu, (int)(ld_relaxed(c) - target) < 0)) {}
}
__device__ __forceinline__ void fence_async_g() { asm volatile("fence.proxy.async.global;" ::: "memory"); }
__device__ __forceinline__ void fence_async_s() { asm volatile("fence.proxy.async.shared::cta;" ::: "memory"); }
#define ELECT "{\n.reg .pred e;\nelect.sync _|e, 0xffffffff;\n@e "
__device__ __forceinline__ void w_expect(uint32_t a, int b) { asm volatile(ELECT "mbarrier.arrive.expect_tx.shared::cta.b64 _, [%0], %1;\n}" ::"r"(a), "r"(b) : "memory"); }
__device__ __forceinline__ void bulk_g2s(uint32_t dst, const void* src, int bytes, uint32_t bar) {
  asm volatile(ELECT "cp.async.bulk.shared::cluster.global.mbarrier::complete_tx::bytes [%0], [%1], %2, [%3];\n}" ::"r"(dst), "l"(src), "r"(bytes), "r"(bar) : "memory");
}
__device__ __forceinline__ void bulk_commit() { asm volatile("cp.async.bulk.commit_group;" ::: "memory"); }
__device__ __forceinline__ void bulk_wait_read0() { asm volatile("cp.async.bulk.wait_group.read 0;" ::: "memory"); }
__device__ __forceinline__ void tma2d(uint32_t dst, const CUtensorMap* m, int c0, int c1, uint32_t bar) {
  asm volatile(ELECT "cp.async.bulk.tensor.2d.shared::cluster.global.mbarrier::complete_tx::bytes [%0], [%1, {%3, %4}], [%2];\n}" ::"r"(dst), "l"(m), "r"(bar), "r"(c0), "r"(c1) : "memory");
}
__device__ __forceinline__ void tma3d(uint32_t dst, const CUtensorMap* m, int c0, int c1, int c2, uint32_t bar) {
  asm volatile(ELECT "cp.async.bulk.tensor.3d.shared::cluster.global.mbarrier::complete_tx::bytes [%0], [%1, {%3, %4, %5}], [%2];\n}" ::"r"(dst), "l"(m), "r"(bar), "r"(c0), "r"(c1), "r"(c2) : "memory");
}
__device__ __forceinline__ void tma_rows(uint32_t dst, const CUtensorMap* m, int c0, int c2, int c3, uint32_t bar) {
  asm volatile(ELECT "cp.async.bulk.tensor.4d.shared::cluster.global.mbarrier::complete_tx::bytes [%0], [%1, {%3, %6, %4, %5}], [%2];\n}" ::"r"(dst), "l"(m), "r"(bar), "r"(c0), "r"(c2), "r"(c3), "r"(0) : "memory");
}
__device__ __forceinline__ void tma_rows_add(const CUtensorMap* m, int c0, int c2, int c3, uint32_t src) {
  asm volatile(ELECT "cp.reduce.async.bulk.tensor.4d.global.shared::cta.add.tile.bulk_group [%0, {%2, %5, %3, %4}], [%1];\n}" ::"l"(m), "r"(src), "r"(c0), "r"(c2), "r"(c3), "r"(0) : "memory");
}
__device__ __forceinline__ void tma5d(uint32_t dst, const CUtensorMap* m, int c0, int c1, int c2, int c3, uint32_t bar) {
  asm volatile(ELECT "cp.async.bulk.tensor.5d.shared::cluster.global.mbarrier::complete_tx::bytes [%0], [%1, {%3, %4, %5, %6, %7}], [%2];\n}" ::"r"(dst), "l"(m), "r"(bar), "r"(c0), "r"(c1), "r"(c2), "r"(c3), "r"(0) : "memory");
}
__device__ __forceinline__ void tma5d_store(const CUtensorMap* m, int c0, int c2, int c3, uint32_t src) {
  asm volatile(ELECT "cp.async.bulk.tensor.5d.global.shared::cta.bulk_group [%0, {%2, %5, %3, %4, %5}], [%1];\n}" ::"l"(m), "r"(src), "r"(c0), "r"(c2), "r"(c3), "r"(0) : "memory");
}
__device__ __forceinline__ void bulk_s2peer(uint32_t rdst, uint32_t src, int bytes, uint32_t rbar) {
  asm volatile(ELECT "cp.async.bulk.shared::cluster.shared::cta.mbarrier::complete_tx::bytes [%0], [%1], %2, [%3];\n}" ::"r"(rdst), "r"(src), "r"(bytes), "r"(rbar) : "memory");
}
__device__ __forceinline__ void w_count(const Scratch* G, int idx) { asm volatile(ELECT "red.relaxed.gpu.global.add.u32 [%0], 1;\n}" ::"l"(G->cnt + idx * 32) : "memory"); }
__device__ __forceinline__ void w_count_timed(const Scratch* G, int idx) {
  asm volatile("{\n.reg .pred e;\n.reg .u64 t;\nelect.sync _|e, 0xffffffff;\nmov.u64 t, %%globaltimer;\n@e red.relaxed.gpu.global.max.u64 [%0+8], t;\n@e red.relaxed.gpu.global.add.u32 [%0], 1;\n}" ::"l"(G->cnt + idx * 32) : "memory");
}
__device__ __forceinline__ void w_arrive(uint32_t a) { asm volatile(ELECT "mbarrier.arrive.shared::cta.b64 _, [%0];\n}" ::"r"(a) : "memory"); }
__device__ __forceinline__ void w_arrive_peer(uint32_t ra) { asm volatile(ELECT "mbarrier.arrive.shared::cluster.b64 _, [%0];\n}" ::"r"(ra) : "memory"); }
__device__ __forceinline__ void tmap_prefetch(const CUtensorMap* m) { asm volatile("prefetch.tensormap [%0];" ::"l"(m) : "memory"); }
__device__ __forceinline__ uint64_t mkdesc(uint32_t addr, uint32_t lbo, uint32_t sbo, uint32_t swz) {
  return (uint64_t)((addr & 0x3FFFF) >> 4) | ((uint64_t)(lbo >> 4) << 16) | ((uint64_t)(sbo >> 4) << 32) | ((uint64_t)swz << 62);
}
#define WG_FENCE() asm volatile("wgmma.fence.sync.aligned;" ::: "memory")
#define WG_COMMIT() asm volatile("wgmma.commit_group.sync.aligned;" ::: "memory")
#define WG_WAIT(n) asm volatile("wgmma.wait_group.sync.aligned " #n ";" ::: "memory")
__device__ __forceinline__ uint32_t lds32(uint32_t a) { uint32_t v; asm volatile("ld.shared.u32 %0, [%1];" : "=r"(v) : "r"(a) : "memory"); return v; }
__device__ __forceinline__ uint2 lds64(uint32_t a) { uint2 v; asm volatile("ld.shared.v2.u32 {%0,%1}, [%2];" : "=r"(v.x), "=r"(v.y) : "r"(a) : "memory"); return v; }
__device__ __forceinline__ uint4 lds128(uint32_t a) { uint4 v; asm volatile("ld.shared.v4.u32 {%0,%1,%2,%3}, [%4];" : "=r"(v.x), "=r"(v.y), "=r"(v.z), "=r"(v.w) : "r"(a) : "memory"); return v; }
__device__ __forceinline__ float4 lds128f(uint32_t a) { float4 v; asm volatile("ld.shared.v4.f32 {%0,%1,%2,%3}, [%4];" : "=f"(v.x), "=f"(v.y), "=f"(v.z), "=f"(v.w) : "r"(a) : "memory"); return v; }
__device__ __forceinline__ void sts32(uint32_t a, uint32_t v) { asm volatile("st.shared.u32 [%0], %1;" ::"r"(a), "r"(v) : "memory"); }
__device__ __forceinline__ void sts64(uint32_t a, uint32_t x, uint32_t y) { asm volatile("st.shared.v2.u32 [%0], {%1,%2};" ::"r"(a), "r"(x), "r"(y) : "memory"); }
__device__ __forceinline__ void sts128(uint32_t a, uint4 v) { asm volatile("st.shared.v4.u32 [%0], {%1,%2,%3,%4};" ::"r"(a), "r"(v.x), "r"(v.y), "r"(v.z), "r"(v.w) : "memory"); }
__device__ __forceinline__ void stsm4(uint32_t a, uint32_t r0, uint32_t r1, uint32_t r2, uint32_t r3) {
  asm volatile("stmatrix.sync.aligned.m8n8.x4.shared.b16 [%0], {%1,%2,%3,%4};" ::"r"(a), "r"(r0), "r"(r1), "r"(r2), "r"(r3) : "memory");
}
__device__ __forceinline__ void stsm4t(uint32_t a, uint32_t r0, uint32_t r1, uint32_t r2, uint32_t r3) {
  asm volatile("stmatrix.sync.aligned.m8n8.x4.trans.shared.b16 [%0], {%1,%2,%3,%4};" ::"r"(a), "r"(r0), "r"(r1), "r"(r2), "r"(r3) : "memory");
}
__device__ __forceinline__ void ldsm4(uint32_t a, uint32_t& r0, uint32_t& r1, uint32_t& r2, uint32_t& r3) {
  asm volatile("ldmatrix.sync.aligned.m8n8.x4.shared.b16 {%0,%1,%2,%3}, [%4];" : "=r"(r0), "=r"(r1), "=r"(r2), "=r"(r3) : "r"(a) : "memory");
}
__device__ __forceinline__ void ldsm4t(uint32_t a, uint32_t& r0, uint32_t& r1, uint32_t& r2, uint32_t& r3) {
  asm volatile("ldmatrix.sync.aligned.m8n8.x4.trans.shared.b16 {%0,%1,%2,%3}, [%4];" : "=r"(r0), "=r"(r1), "=r"(r2), "=r"(r3) : "r"(a) : "memory");
}
__device__ __forceinline__ void hmma(float* d, uint32_t a0, uint32_t a1, uint32_t a2, uint32_t a3, uint32_t b0, uint32_t b1) {
  asm volatile("mma.sync.aligned.m16n8k16.row.col.f32.bf16.bf16.f32 {%0,%1,%2,%3}, {%4,%5,%6,%7}, {%8,%9}, {%0,%1,%2,%3};"
               : "+f"(d[0]), "+f"(d[1]), "+f"(d[2]), "+f"(d[3]) : "r"(a0), "r"(a1), "r"(a2), "r"(a3), "r"(b0), "r"(b1));
}
__device__ __forceinline__ void stg32_if(bool on, void* p, uint32_t v) {
  asm volatile("{\n.reg .pred p;\nsetp.ne.b32 p, %2, 0;\n@p st.global.u32 [%0], %1;\n}" ::"l"(p), "r"(v), "r"((int)on) : "memory");
}
__device__ __forceinline__ void ldg128_if(bool on, const void* p, uint32_t* v) {
  asm volatile("{\n.reg .pred p;\nsetp.ne.b32 p, %5, 0;\n@p ld.relaxed.gpu.global.v4.u32 {%0,%1,%2,%3}, [%4];\n}" : "=r"(v[0]), "=r"(v[1]), "=r"(v[2]), "=r"(v[3]) : "l"(p), "r"((int)on) : "memory");
}
__device__ __forceinline__ void sts32(uint32_t a, uint32_t v, bool on) { if (on) sts32(a, v); }
__device__ __forceinline__ void ldsm4_if(bool on, uint32_t a, uint32_t* v) {
  asm volatile("{\n.reg .pred p;\nsetp.ne.b32 p, %5, 0;\n@p ldmatrix.sync.aligned.m8n8.x4.shared.b16 {%0,%1,%2,%3}, [%4];\n}" : "+r"(v[0]), "+r"(v[1]), "+r"(v[2]), "+r"(v[3]) : "r"(a), "r"((int)on) : "memory");
}
__device__ __forceinline__ void lds32_if(bool on, uint32_t& v, uint32_t a) {
  asm volatile("{\n.reg .pred p;\nsetp.ne.b32 p, %2, 0;\n@p ld.shared.u32 %0, [%1];\n}" : "=r"(v) : "r"(a), "r"((int)on) : "memory");
}
__device__ __forceinline__ void st_peer4(uint32_t ra, const uint4* v, uint32_t rbar) {
#define SP(o, a, b, c, d) "st.async.weak.shared::cluster.mbarrier::complete_tx::bytes.v4.b32 [%0+" #o "], {%" #a ",%" #b ",%" #c ",%" #d "}, [%1];\n"
  asm volatile(SP(0, 2, 3, 4, 5) SP(512, 6, 7, 8, 9) SP(1024, 10, 11, 12, 13) SP(1536, 14, 15, 16, 17)
               ::"r"(ra), "r"(rbar), "r"(v[0].x), "r"(v[0].y), "r"(v[0].z), "r"(v[0].w), "r"(v[1].x), "r"(v[1].y), "r"(v[1].z), "r"(v[1].w),
                 "r"(v[2].x), "r"(v[2].y), "r"(v[2].z), "r"(v[2].w), "r"(v[3].x), "r"(v[3].y), "r"(v[3].z), "r"(v[3].w) : "memory");
}
__device__ __forceinline__ uint32_t ldg32(const void* p) { uint32_t v; asm volatile("ld.global.nc.u32 %0, [%1];" : "=r"(v) : "l"(p)); return v; }
__device__ __forceinline__ uint32_t ldg16(const void* p) { uint16_t v; asm volatile("ld.global.nc.u16 %0, [%1];" : "=h"(v) : "l"(p)); return v; }
__device__ __forceinline__ uint32_t pack2(float lo, float hi) { uint32_t d; asm("cvt.rn.bf16x2.f32 %0, %1, %2;" : "=r"(d) : "f"(hi), "f"(lo)); return d; }
__device__ __forceinline__ float blo(uint32_t x) { return __uint_as_float(x << 16); }
__device__ __forceinline__ float bhi(uint32_t x) { return __uint_as_float(x & 0xffff0000u); }
__device__ __forceinline__ float bround(float x) { return bhi(pack2(0.f, x)); }
__device__ __forceinline__ uint32_t bmul2(uint32_t a, uint32_t b) { uint32_t d; asm("mul.rn.bf16x2 %0, %1, %2;" : "=r"(d) : "r"(a), "r"(b)); return d; }
__device__ __forceinline__ uint32_t badd2(uint32_t a, uint32_t b) { uint32_t d; asm("add.rn.bf16x2 %0, %1, %2;" : "=r"(d) : "r"(a), "r"(b)); return d; }
__device__ __forceinline__ uint32_t bfma2(uint32_t a, uint32_t b, uint32_t c) { uint32_t d; asm("fma.rn.bf16x2 %0, %1, %2, %3;" : "=r"(d) : "r"(a), "r"(b), "r"(c)); return d; }
__device__ __forceinline__ float silu(float x) { return __fdividef(x, 1.f + __expf(-x)); }
__device__ __forceinline__ float gelu2(float a, float k1, float k2) {
  float u, t;
  asm volatile("mul.rn.f32 %0, %1, %1;" : "=f"(u) : "f"(a));
  asm("tanh.approx.f32 %0, %1;" : "=f"(t) : "f"(a * fmaf(u, k2, k1)));
  asm volatile("fma.rn.f32 %0, %0, %1, %0;" : "+f"(a) : "f"(t));
  return a;
}
__device__ __forceinline__ void stage_end() { asm volatile("pmevent 1;"); }
__device__ __forceinline__ uint32_t bdup(uint32_t x, int hi) {
  uint32_t d;
  if (hi) asm("{\n.reg .b16 l, h;\nmov.b32 {l, h}, %1;\nmov.b32 %0, {h, h};\n}" : "=r"(d) : "r"(x));
  else asm("{\n.reg .b16 l, h;\nmov.b32 {l, h}, %1;\nmov.b32 %0, {l, l};\n}" : "=r"(d) : "r"(x));
  return d;
}
__device__ __forceinline__ uint32_t baffine(uint32_t x, uint32_t c) {
  uint32_t d;
  asm("{\n.reg .b16 l, h;\n.reg .b32 a, b;\nmov.b32 {l, h}, %2;\nmov.b32 a, {l, l};\nmov.b32 b, {h, h};\nfma.rn.bf16x2 %0, %1, a, b;\n}" : "=r"(d) : "r"(x), "r"(c));
  return d;
}
__device__ __forceinline__ uint32_t clk32() { uint32_t t; asm volatile("mov.u32 %0, %%clock;" : "=r"(t)::"memory"); return t; }
__device__ __forceinline__ void sleep_until(uint32_t t0) {
  asm volatile("{\n.reg .pred p;\n.reg .s32 t;\nSL:\nmov.u32 t, %%clock;\nsub.s32 t, t, %0;\nsetp.lt.s32 p, t, 0;\n@p nanosleep.u32 20;\n@p bra.uni SL;\n}" ::"r"(t0) : "memory");
}
__device__ __forceinline__ void sleep_for(uint32_t d) { sleep_until(__shfl_sync(0xffffffffu, clk32() + d + (threadIdx.x & 31), 0)); }

#define TSP(mask, on, id) do {} while (0)
#define TSX(mask, id) do {} while (0)
#define TGX(id) do {} while (0)
#define FX(id) do {} while (0)
#define TS1(id) TSX(1, id)
#define TS2(id) TSX(2, id)
#define TS3(id) TSX(4, id)
#define TSS(id) TSX(7, id)
#define W0(id) (w == 0 ? (id) : 127)

template <int N>
__device__ __forceinline__ void bfly(float* v, int lane, int mask) {
  const bool b = lane & mask;
#pragma unroll
  for (int i = 0; i < N / 2; i++) {
    float mine = b ? v[i + N / 2] : v[i], other = b ? v[i] : v[i + N / 2];
    v[i] = mine + __shfl_xor_sync(0xffffffffu, other, mask);
  }
}
__device__ __forceinline__ float quad_sum(float x) { x += __shfl_xor_sync(0xffffffffu, x, 1); return x + __shfl_xor_sync(0xffffffffu, x, 2); }

template <int N>
__device__ __forceinline__ void conv_tri(float* acc, uint32_t (*A)[4], uint64_t db) {
  if constexpr (N == 128) wrs128_first(acc, A[0], db); else WRS<N>::mma(acc, A[0], db);
  if constexpr (N > 16) conv_tri<N - 16>(acc, A + 1, db + 16);
}
__device__ __forceinline__ void conv_mma(float* acc, uint32_t (*A)[4], uint64_t db) {
  WG_FENCE();
  conv_tri<128>(acc, A + 8, db + 128);
  WG_COMMIT();
  WG_FENCE();
  WRS<128>::mma(acc, A[7], db + 112); WRS<128>::mma(acc, A[6], db + 96);
  WG_COMMIT();
  WG_WAIT(1);
  WG_FENCE();
  conv_tri<128>(acc + 64, A, db + 128);
#pragma unroll
  for (int T = 5; T >= 0; T--) WRS<128>::mma(acc, A[T], db + 16 * T);
  WG_COMMIT();
}
template <int N>
__device__ __forceinline__ void zero_acc(float* a) {
#pragma unroll
  for (int i = 0; i < N; i += 2) asm volatile("mov.b64 {%0, %1}, 0;" : "=f"(a[i]), "=f"(a[i + 1]));
}
template <int N>
__device__ __forceinline__ void undef(float* a) {
#pragma unroll
  for (int i = 0; i < N; i++) asm volatile("" : "=f"(a[i]));
}
__device__ __forceinline__ uint32_t ext_frag(float mu, float sg, int q) {
  const float mh = bround(-mu), sh = bround(sg);
  const float lo = q == 0 ? mh : q == 1 ? -mu - mh : sh, hi = q == 0 ? mh : q == 1 ? sh : sg - sh;
  return pack2(lo, hi) & (q == 3 ? 0u : ~0u);
}
__device__ __forceinline__ uint32_t opaque(uint32_t x) { asm volatile("" : "+r"(x)); return __shfl_sync(0xffffffffu, x, 0); }
__device__ __forceinline__ uint32_t tagw(uint32_t x, uint32_t par) { return (x & ~1u) | par; }
__device__ __forceinline__ uint32_t bitsel(uint32_t x, uint32_t y, uint32_t mask) { return (x & ~mask) | (y & mask); }
__device__ __forceinline__ uint32_t stale(uint32_t acc, uint32_t x, uint32_t par) { uint32_t d; asm("lop3.b32 %0, %1, %2, %3, 0xf6;" : "=r"(d) : "r"(acc), "r"(x), "r"(par)); return d; }
__device__ __forceinline__ bool any_stale(uint32_t acc) { return __builtin_expect(__any_sync(0xffffffffu, acc & 1), 0); }
__device__ __forceinline__ uint32_t sum2(uint32_t a, uint32_t b, uint32_t c, uint32_t d) { return pack2(__uint_as_float(a) + __uint_as_float(b), __uint_as_float(c) + __uint_as_float(d)); }
__device__ __forceinline__ uint32_t ln3(float s, float q, float eps) {
  const float mu = s * (1.f / 864.f), c = rsqrtf(fmaxf(q * (1.f / 864.f) - mu * mu, 0.f) + eps);
  return pack2(c, -mu * c);
}
__device__ __forceinline__ void refetch(uint32_t ta, const uint4* gp, uint32_t wo, uint32_t par) {
  bool again;
#pragma unroll 1
  do { again = any_stale(lds32(ta + wo) ^ par); sts128(ta, ld_relaxed4(gp)); sts128(ta + 16, ld_relaxed4(gp + 1)); } while (again);
  fence_async_s();
}

__global__ void __cluster_dims__(2, 1, 1) __launch_bounds__(512, 1)
fused_kernel(const __grid_constant__ Params p, const __grid_constant__ Maps tm) {
  extern __shared__ __align__(1024) unsigned char smem_raw[];
  const uint32_t tstart = __shfl_sync(0xffffffffu, clk32() + (threadIdx.x & 31), 0);
  const uint32_t sb = __shfl_sync(0xffffffffu, (uint32_t)__cvta_generic_to_shared(smem_raw), 0);
  const int tid = threadIdx.x, lane = tid & 31;
  const int warp = __shfl_sync(0xffffffffu, tid >> 5, 0);
  const int wg = warp >> 2, w = warp & 3, t128 = tid & 127;
  const int r = lane >> 2, q = lane & 3, mi = lane >> 3, rr = lane & 7;
  Scratch* const G = p.g;
  auto BAR = [&](int i) { return sb + SM_BAR + i * 8; };
  if (warp == 15) asm volatile("{\n.reg .u32 t;\nld.relaxed.gpu.global.u32 t, [%0];\nshr.u32 t, t, 6;\nredux.sync.min.u32 t, t, 0xffffffff;\nadd.u32 t, t, 1;\nst.shared.u32 [%1], t;\n}"
                               ::"l"(G->cnt + min(lane, C_E + 1) * 32), "r"(sb + SM_TPC + 4) : "memory");
  unsigned crank, mytpc;
  asm("mov.u32 %0, %%smid;" : "=r"(mytpc));
  asm("mov.u32 %0, %%cluster_ctarank;" : "=r"(crank));
  mytpc = (p.by_sm ? mytpc : blockIdx.x) >> 1;
  const int bid = (mytpc < 60 ? mytpc : mytpc < 62 ? mytpc + 4 : mytpc - 2) * 2 + crank;
  if ((warp >> 1) == 4 && bid < 128) asm volatile("prefetch.global.L2 [%0];" ::"l"((&p.k)[w] + ((bid >> 1) * 32 + lane) * 640 + crank * 64));
  if (warp > 4 && warp < 8) asm volatile(ELECT "prefetch.tensormap [%0];\n}" ::"l"(&tm.k + (7 - warp)) : "memory");
#define BI(o) "@e mbarrier.init.shared::cta.b64 [%0+" #o "], %1;\n"
  if (warp == 12 && bid < 128) {
    asm volatile("{\n.reg .pred e;\nelect.sync _|e, 0xffffffff;\n" BI(0) "fence.mbarrier_init.release.cluster;\n}" ::"r"(BAR(B_KV)), "r"(1) : "memory");
    w_expect(BAR(B_KV), 11520 + 5120);
    tma5d(sb, &tm.k, crank * 64, 0, (bid >> 1) * 4 - 1, 0, BAR(B_KV));
    tma5d(sb + KV_V, &tm.v, crank * 64, 0, (bid >> 1) * 4, 0, BAR(B_KV));
    bulk_g2s(sb + SM_S, p.shiftk, 5120, BAR(B_KV));
  }
  if (warp < 4) {
#pragma unroll 1
    for (int g = warp; g < 16; g += 4)
      asm volatile("{\n.reg .pred e;\nelect.sync _|e, 0xffffffff;\n" BI(8) BI(16) BI(24) BI(32) BI(40) BI(48) BI(56) "fence.mbarrier_init.release.cluster;\n}"
                   ::"r"(BAR(g * 7)), "r"(g < 7 ? (bid >= 128 && !g ? 14 : 1) : g < 9 ? 2 : 4) : "memory");
  }
  if (tid == 96) sts32(sb + SM_TPC, mytpc);
  asm volatile("barrier.cluster.arrive.relaxed.aligned;" ::: "memory");
  auto READY = [&]() { asm volatile("barrier.cluster.wait.aligned;" ::: "memory"); };
  auto EPOCH = [&]() { return lds32(sb + SM_TPC + 4); };
  if (wg == 1 && bid < 128) {
    const int it = (int)(SEQ0 >> (16 + 8 * w)), ty = (it >> 4) & 3, s = it & 15;
    const uint32_t fb = BAR((ty >> 1) * 5 + s);
    READY();
    if (ty != 1) w_expect(fb, ty ? 4096 : 11520);
    sleep_until(tstart + T_2 + w * PACE_D);
    tma5d(sb + (ty == 2 ? offF(s) + 16 : s * 16384 + ty * KV_V), &tm.k + ty, ty == 2 ? 0 : s * 128 + crank * 64, 0, ty == 2 ? s * 128 + bid : (bid >> 1) * 4 - 1 + ty, 0, fb);
    TSX(17, 104 + w);
  }

  if (bid >= 128) {
    const int j = bid - 128;
    READY();
    constexpr uint32_t S_TAB = SM_S;
    if (warp < 14) {
      const unsigned tag = EPOCH(), par = tag & 1;
      const uint32_t to = sb + S_TAB + (tid >> 2) * 64 + q * 8;
      st_relaxed4(G->vt + (tid < 224 ? j * 224 : (3 + j) * 224) + tid, make_uint4(0, 0, 0, (tag - 1) & 0x3fff));
      if (tid < 192 && j * 192 + tid < 640) st_relaxed(G->gb + j * 192 + tid, par ^ 1);
      if (tid < 160) {
        const uint32_t c0 = ldg32(p.c + (tid >> 2) * 16 + q * 2), c1 = ldg32(p.c + (tid >> 2) * 16 + q * 2 + 8);
        sts64(to + 4096, pack2(silu(blo(c0)), silu(bhi(c0))), pack2(silu(blo(c1)), silu(bhi(c1))));
        sleep_until(tstart + 9000);
        wait_cnt(G->cnt + (C_M + (lane & 1)) * 32, tag * 64u);
        const uint4* mp = (const uint4*)(G->modp + 1920) + tid;
        uint4 a, b, c, d;
#pragma unroll 1
        do {
          a = ld_relaxed4(mp); b = ld_relaxed4(mp + 800); c = ld_relaxed4(mp + 160); d = ld_relaxed4(mp + 960);
        } while (any_stale(stale(stale(stale(a.x ^ par, b.x, par), c.x, par), d.x, par)));
        sts64(to, badd2(sum2(c.x, d.x, c.z, d.z), 0x3f803f80), badd2(sum2(c.y, d.y, c.w, d.w), 0x3f803f80));
        sts64(to + 32, sum2(a.x, b.x, a.z, b.z), sum2(a.y, b.y, a.w, b.w));
      }
      bar_sync(1, 448);
      TSS(warp == 0 ? 10 : 127);
            int st = 0, ph = 0;
#pragma unroll 1
      for (int part = 0; part < 3; part++) {
        float d[2][4] = {{0.f, 0.f, 0.f, 0.f}, {0.f, 0.f, 0.f, 0.f}};
        const int ch = 2 * warp + (mi & 1) + (part < 2 && part == (j == 1) ? 4 : 0);
        const uint32_t ao = sb + (ch >> 3) * 8192 + (rr + (mi >> 1) * 8) * 128 + (((ch & 7) ^ rr) << 4);
#pragma unroll 1
        for (int u = 0; u < 10; u++) {
          uint32_t a[4][4];
          uint2 b[4];
#pragma unroll
          for (int i = 0; i < 4; i++) b[i] = lds64(sb + S_TAB + (part >> 1) * 4096 + (u * 4 + i) * 64 + (r & 1) * 32 + q * 8);
          mbar_wait(BAR(B_FULL1 + st), ph);
#pragma unroll
          for (int i = 0; i < 4; i++) ldsm4t(ao + st * 32768 + i * 2048, a[i][0], a[i][1], a[i][2], a[i][3]);
#pragma unroll
          for (int i = 0; i < 4; i++) hmma(d[i & 1], a[i][0], a[i][1], a[i][2], a[i][3], b[i].x, b[i].y);
          w_arrive(BAR(1 + st));
          if (++st == 6) { st = 0; ph ^= 1; }
        }
#pragma unroll
        for (int i = 0; i < 2; i++) {
          const float a = d[0][2 * i] + d[1][2 * i], b = d[0][2 * i + 1] + d[1][2 * i + 1], ah = bround(a), bh = bround(b);
          const int cc = warp * 16 + i * 8 + r;
          if (q == 0 && part < 2) st_relaxed4(G->vt + (part * 4 + j) * 224 + cc, make_uint4(pack2(ah, a - ah), pack2(ah, bh), pack2(b - bh, bh), tag & 0x3fff));
          if (q == 0 && part == 2 && cc < 192 && j * 192 + cc < 640) st_relaxed(G->gb + j * 192 + cc, __float_as_uint(ah) | par);
        }
        TSS(warp == 0 ? 1 + part : 127);
      }
    } else if (warp == 14) {
      sleep_until(tstart + T_SPARE);
      uint32_t fb = BAR(B_FULL1), dst = sb, ph = 1;
#pragma unroll 1
      for (int part = 0; part < 3; part++) {
        const int c0 = part == 2 ? 50 + j * 3 : ((part ? 0 : 864) + nstart(j)) >> 6;
#pragma unroll 1
        for (int row = 0; row < 640; row += 64) {
          mbar_wait(fb - (B_FULL1 - 1) * 8, ph);
#pragma unroll 1
          for (int x = 0; x < 2; x++) { w_expect(fb, 16384); tma3d(dst + x * 16384, part == 2 ? &tm.wm2 : &tm.w2, 0, row, c0 + x * 2, fb); }
          fb += 8; dst += 32768;
          if (dst == sb + 196608) { fb -= 48; dst = sb; ph ^= 1; }
        }
      }
    } else {
      const unsigned tag = EPOCH();
#pragma unroll 1
      for (int spin = 0; __any_sync(0xffffffffu, (int)(ld_relaxed(G->cnt + (C_E + (lane & 1)) * 32) - tag * 64u) < 0); spin++) { if (spin > (1 << 18)) __trap(); __nanosleep(500); }
    }
    return;
  }
  const int m = p.tile[bid >> 1] >> 1, n = (p.tile[bid >> 1] & 1) * 2 + crank;
  const uint32_t peer = mapa(sb, crank ^ 1) - sb;

  unsigned tag = 0, par = 0;
  if (wg == 3) {
    asm volatile("setmaxnreg.dec.sync.aligned.u32 32;");
    auto pf_wsp = [&](int i) {
      const __nv_bfloat16* a = p.wsp + ((m >> 1) * 128 + (m & 1) * 32 + lane) * 2048 + ((i + ROT * (m >> 3)) & 15) * 128 + (i >> 4) * 64;
      asm volatile("prefetch.global.L2 [%0];\nprefetch.global.L2 [%0+262144];" ::"l"(a));
    };
    if (w == 3) {
      READY();
      TS1(103);
      const unsigned tag = EPOCH();
      TS1(100);
      if (lane < 9) mbar_expect(BAR(B_AP + lane), lane < 5 ? 8192 : lane < 7 ? (lane - 4) * 1024 : 14336);
      if (lane < 10) mbar_expect(BAR(B_U + lane), lane < 5 ? 4096 : 8192);
#pragma unroll 1
      for (int s = 0; s < 5; s++) {
        if (s && lane < 2) tmap_prefetch(&tm.wm + 2 * s - 2 + lane);
        mbar_wait(BAR(s < HINT_A ? B_KV + s : B_KVF + s), 0);
        if (s < NAPS) sleep_for(NAPA);
        wait_cnt(G->cnt + (C_A + 2 * s + (bid >> 6)) * 32, tag * 64u);
        bulk_g2s(sb + offU(s), G->T + (s * 128 + bid) * 256, 4096, BAR(B_U + s));
        TS1(80 + s);
      }
      {
        uint32_t t;
        asm volatile("ld.shared::cluster.u32 %0, [%1];" : "=r"(t) : "r"(sb + SM_TPC + peer) : "memory");
        if (t != mytpc) __trap();
        unsigned todo = 31;
        mbar_wait(BAR(B_WMF), 0);
#pragma unroll 1
        do {
          unsigned rdy = __ballot_sync(0xffffffffu, ((todo >> lane) & 1) && (int)(ld_relaxed(G->cnt + (C_Y + 2 * lane + crank) * 32) - tag * 64u) >= 0);
          todo &= ~rdy;
#pragma unroll 1
          for (; rdy; rdy &= rdy - 1) {
            const int s = __ffs(rdy) - 1;
            tma3d(sb + s * 16384 + (crank ^ 1) * 8192, &tm.y, 0, s * 128 + crank * 64, m * 2, BAR(B_YH + s));
            TS1(85 + s);
          }
        } while (todo);
      }
#pragma unroll 1
      for (int part = 0; part < 2; part++) {
        const uint4* vp = G->vt + (part * 4 + n) * 224;
        if (STOP_AFTER >= 2) mbar_wait2(BAR(part ? B_VTF : B_AO), BAR(B_AO + 1 + H2), 0, 0);
#pragma unroll 1
        while (__any_sync(0xffffffffu, ld_relaxed(&vp[223].w) != (tag & 0x3fff))) {}
        unsigned bad, ph = 1;
#pragma unroll 1
        do {
          w_expect(BAR(B_U + part), 3584); bulk_g2s(sb + (STOP_AFTER >= 2 ? SM_VT : SM_X1), vp, 3584, BAR(B_U + part));
          mbar_wait(BAR(B_U + part), ph);
          ph ^= 1; bad = 0;
#pragma unroll
          for (int k = 0; k < 7; k++) bad |= lds32(sb + (STOP_AFTER >= 2 ? SM_VT : SM_X1) + k * 512 + lane * 16 + 12) ^ tag;
        } while (__any_sync(0xffffffffu, bad & 0x3fff));
        w_arrive(BAR(B_VT));
        TS2(75 + part);
      }
      if (STOP_AFTER >= 2) {
        pf_wsp(20 + n);
        {
          const uint2* sp = G->st3 + m * 256 + 32 + lane;
          uint2 a, b, c, d;
          mbar_wait(BAR(B_G1), 0);
          sleep_for(WAIT1);
#pragma unroll 1
          do { a = ld_relaxed2(sp); b = ld_relaxed2(sp + 64); c = ld_relaxed2(sp + 128); d = ld_relaxed2(sp + 192); } while (any_stale(stale(stale(stale(a.x ^ tag, b.x, tag), c.x, tag), d.x, tag)));
          sts32(sb + SM_LNB + lane * 4, ln3((__uint_as_float(a.x) + __uint_as_float(b.x)) + (__uint_as_float(c.x) + __uint_as_float(d.x)),
                                            (__uint_as_float(a.y) + __uint_as_float(b.y)) + (__uint_as_float(c.y) + __uint_as_float(d.y)), __uint_as_float(lds32(sb + SM_LNB + lane * 4))));
          w_arrive(BAR(B_CP));
          TS2(69);
        }
        mbar_wait2(BAR(B_PUB), BAR(B_X1D), 0, 0);
#pragma unroll 1
        for (int h = 0; h < 2; h++) {
          if (h) { fence_async_g(); fence_gpu(); }
          w_count(G, C_H + 2 * h + crank);
          TS2(77 + h);
          pf_wsp(24 + 4 * h + n);
          sleep_for(POLL1);
#pragma unroll 1
          while (__any_sync(0xffffffffu, (int)(ld_acquire(G->cnt + (C_H + 2 * h + (lane & 1)) * 32) - tag * 64u) < 0)) {}
          w_arrive(BAR(B_LOK + 1 + h));
          TS2(91 + h);
        }
        fence_async_g();
        if (lane == 0) asm volatile("cp.async.bulk.prefetch.L2.global [%0], 8640;" ::"l"(p.wout + bid * 4320) : "memory");
      }
      if (STOP_AFTER >= 4) {
#pragma unroll 1
        for (int s = 0; s < 5; s++) {
          uint2 a;
#pragma unroll 1
          for (;;) { a = ld_relaxed2(G->gb + s * 128 + crank * 64 + lane * 2); if (!any_stale(stale(a.x ^ tag, a.y, tag))) break; __nanosleep(200); }
          sts32(sb + SM_GB + s * 128 + (r >> 2) * 64 + q * 16 + (r & 3) * 4, __byte_perm(a.x, a.y, 0x7632));
        }
        w_arrive(BAR(B_GB));
      }
      goto done;
    }
    if (w == 2) {
      const uint32_t dsk = ldg16(p.ssmD + min(lane, 4) * 128 + bid);
      READY();
#pragma unroll 1
      for (int s = 0; s < 5; s++) {
        const uint32_t fE = sb + offF(s) + 16 + lane * 16, dk = __shfl_sync(0xffffffffu, dsk, s);
        mbar_wait(BAR(B_F + s), 0);
        TSX(17, 70 + s);
#pragma unroll 1
        for (int o = 2048; o >= 0; o -= 2048) {
          uint4 e[4];
          uint32_t nx[4];
#pragma unroll
          for (int i = 0; i < 4; i++) { e[i] = lds128(fE + o + i * 512); nx[i] = lds32(fE + o + i * 512 + 16); }
          if (lane + o == 0) { const uint32_t f0 = pack2(blo(e[0].x) + blo(dk), bhi(e[0].x)); sts32(fE, f0); sts32(fE + 4156, f0 << 16); }
#pragma unroll
          for (int i = 0; i < 4; i++) sts128(fE + o + 4160 + i * 512, make_uint4(__byte_perm(e[i].x, e[i].y, 0x5432), __byte_perm(e[i].y, e[i].z, 0x5432), __byte_perm(e[i].z, e[i].w, 0x5432), __byte_perm(e[i].w, nx[i], 0x5432)));
        }
        asm volatile(ELECT "mbarrier.arrive.shared::cta.b64 _, [%0], 4;\n}" ::"r"(BAR(B_FO + s)) : "memory");
        TS1(75 + s);
      }
    }
    if (w < 2) {
      {
        const int it = (int)(((lane < 8 ? SEQ0 : lane < 16 ? SEQ1 : lane < 24 ? SEQ2 : SEQ3) >> (8 * rr)) & 255), ty = it >> 4, s = it & 15;
        const bool on = lane < 25 && (ty != 3 || bid < 100);
        const uint32_t bi = ty == 4 ? B_Q + (s > 2) : max(ty - 1, 0) * 5 + s;
        const uint32_t a0 = ty == 3 ? (bid >> 1) * 64 + ((crank * 320 + s * 64) << 16) : ty == 2 ? 0 : s * 128 + crank * 64;
        const uint32_t a1 = ty < 2 ? ((bid >> 1) * 4 - 1 + ty) << 8 : ty == 2 ? (s * 128 + bid) << 8 : ty == 3 ? 0 : ((m & ~1) << 8) + (m & 1) * 4;
        const uint32_t a2 = (ty == 2 ? offF(s) + 16 : s * 16384 + (ty < 2 ? ty * KV_V : ((ty ^ crank) & 1) * 8192)) + ty + (bi << 18) + ((B_KVF + s) << 24);
        const uint32_t a3 = tstart + T_2 - 2 * PACE_D + lane * PACE_D + max(lane - 13, 0) * (PACE_F - PACE_D) + __popc(__ballot_sync(0xffffffffu, ty == 3) << (31 - lane) << 1) * (PACE_W - PACE_F) + max(lane - 20, 0) * (PACE_Q - PACE_F);
        unsigned todo = __ballot_sync(0xffffffffu, on) & (0x55555555u << (6 + w));
        READY();
        if (on && ty != 1 && (it <= 0x40 || it == 0x44) && lane > 5 && !w) mbar_expect(BAR(bi), ty == 0 ? 11520 : ty == 2 ? 4096 : ty == 3 ? 8192 : 24576 - s * 2048);
#pragma unroll 1
        while (todo) {
          const int i = __ffs(todo) - 1;
          const uint32_t b0 = __shfl_sync(0xffffffffu, a0, i), b1 = __shfl_sync(0xffffffffu, a1, i), b2 = __shfl_sync(0xffffffffu, a2, i);
          todo &= todo - 1;
          sleep_until(__shfl_sync(0xffffffffu, a3, i));
          TSX(16, 1 + i); TSP(1, i < 10, 90 + i);
          if ((b2 & 7) > 2) mbar_wait(BAR(b2 >> 24), 0);
          tma5d(sb + (b2 & 0x3ff80), &tm.k + (b2 & 7), b0 & 0xffff, b0 >> 16, (int)b1 >> 8, b1 & 255, BAR((b2 >> 18) & 63));
        }
      }
      TS1(w == 0 ? 95 : 127);
    }
    if (w) {
      const int x = w - 1;
      if (STOP_AFTER >= 2) {
        if (lane == 0) tmap_prefetch(&tm.w3 + x);
        sleep_until(tstart + T_WIN);
#pragma unroll 1
        for (int g = 0; g < 20; g++) {
          const int base = (g < 10 ? 864 : 0) + nstart(n), row = ((g < 10 ? g : g - 10) ^ crank) * 64;
          const uint32_t fb = BAR(B_FULL1 + (g & 3)), dst = sb + SM_R + (g & 3) * 32768;
          mbar_wait(fb + (B_EMPTY1 - B_FULL1) * 8, (g >> 2) & 1);
          if (x) { w_expect(fb, 4096); tma2d(dst + 24576, &tm.wn, base + ((base & 32) ? 0 : 192), row, fb); }
          else { w_expect(fb, 24576); tma3d(dst, &tm.w3, 0, row, (base + 32) >> 6, fb); }
        }
      }
    } else {
      const unsigned tag = lds32(sb + SM_TPC + 4);
      mbar_wait(BAR(B_WMF), 0);
      if (NAPM) sleep_for(NAPM);
      wait_cnt(G->cnt + (C_M + (lane & 1)) * 32, tag * 64u);
      w_arrive(BAR(B_YH + 5));
      TS1(90);
      if (STOP_AFTER >= 2) {
#pragma unroll 1
        for (int s = 0; s < 5; s++) {
          mbar_wait(BAR(B_AO + s), 0);
          pf_wsp(4 * s + n);
        }
        mbar_wait(BAR(B_AP + 4), 0);
#pragma unroll 1
        for (int s = 0; s < 5; s++) {
          tma5d_store(&tm.x1, s * 128 + crank * 64, m & ~1, (m & 1) * 4 + (n & 2), sb + offX(s));
          sleep_for(XGAP);
        }
        bulk_commit();
        asm volatile("cp.async.bulk.wait_group 0;" ::: "memory");
        w_arrive(BAR(B_X1D));
      }
      if (STOP_AFTER >= 3) {
        mbar_wait(BAR(B_G0), 0);
        sleep_for(POLL0);
        TS2(100);
        uint4 c;
#pragma unroll 1
        do c = ld_relaxed4(G->cnt + (C_G + (lane & 1)) * 32); while (__any_sync(0xffffffffu, (int)(c.x - tag * 64u) < 0));
        TS2(101);
#pragma unroll 1
        for (;;) {
          uint32_t t;
          asm volatile("mov.u32 %0, %%globaltimer_lo;" : "=r"(t)::"memory");
          if (__all_sync(0xffffffffu, t - c.z >= DELAY0)) break;
        }
        w_arrive(BAR(B_LOK));
      }
    }
    if (STOP_AFTER >= 3) {
      const uint4* zp = G->z2n + n * 32 * IMG;
      uint32_t off = 0, ph = 0;
      mbar_wait(BAR(w == 1 ? B_X1D : B_LOK), 0);
#pragma unroll 1
      for (int i = 0; i < 32; i++) {
        const int M = (i + ROT * (m >> 3)) & 15;
        const uint32_t fb = BAR(B_FULL2) + off, dst = sb + (((uint32_t)((w == 1 ? 0x40906C1CD8ull : 0x9874245000ull) >> off) & 255) << 10);
        if (i == 16) mbar_wait(BAR(B_LOK + 1), 0);
        mbar_wait(fb + (B_EMPTY2 - B_FULL2) * 8, ph);
        if (!w && (i < 10 || i == 16)) TS2(min(80 + i, 90));
        TSP(8, (i & 1) * 2 == w && i < 15, 81 + i);
        if (w == 1) { if (i < 15) TSX(8, 101 + i);  w_expect(fb, 8192); tma_rows(dst, &tm.wsp, M * 128 + (i >> 4) * 64, m & ~1, (m & 1) * 4, fb); }
        else if ((i & 1) * 2 == w) { w_expect(fb, 28672); bulk_g2s(dst, zp + ((i & 16) + M) * IMG, 28672, fb); }
        off += 8;
        if (off == 40) { off = 0; ph ^= 1; }
      }
    }
    if (w) {
      const int x = w - 1;
      if (STOP_AFTER >= 4) {
#pragma unroll 1
        for (int k = 0; k < 10; k++) {
          const int st = 1 + ((k + 1) & 3);
          const uint32_t fb = BAR(B_FULL2 + st);
          mbar_wait(fb + (B_EMPTY2 - B_FULL2) * 8, ((k + 1) >> 2) & 1);
          TS3(x ? 127 : 60 + k);
          w_expect(fb, 14336);
          tma2d(sb + placeB(st) + x * 14336, &tm.wo, (k < 8 ? ((k ^ (n & BOXX)) & 2) + x : 4) * 128 + crank * 64, nstart(n ^ (k < 8 ? k >> 2 : k & 1)) + 112 * (k < 8 ? k & 1 : x), fb);
        }
      }
    } else {
      if (STOP_AFTER >= 4) mbar_wait(BAR(B_GB), 0);
      w_count(G, C_E + crank);
      if (STOP_AFTER >= 4) {
        mbar_wait_b(BAR(B_PFREE), 0);
#pragma unroll 1
        for (int e = 0; e < 2; e++) {
          mbar_wait_b(BAR(B_PST + max(e, PONE)), 0);
          if (e) { mbar_wait_b(BAR(B_EMPTY2 + PGATE), 1); sleep_for(100); }
          bulk_s2peer(sb + e * 14336 + peer, sb + SM_PO + e * 14336, 14336, BAR(B_PP + e) + peer);
        }
        mbar_wait_b(BAR(B_PP), 0);
        TS3(24);
        mbar_wait_b(BAR(B_PP + 1), 0);
        TS3(25);
        w_arrive_peer(BAR(B_ACK) + peer);
        mbar_wait_b(BAR(B_ACK), 0);
      }
      w_arrive(BAR(B_DONE + 3));
#pragma unroll 1
      for (int i = 3; i >= 0; i--) mbar_wait_b(BAR(B_DONE + i), 0);
      return;
    }
    goto done;
  }
  if (wg < 2) {
    sleep_until(tstart + T_AB);
    asm volatile("setmaxnreg.inc.sync.aligned.u32 192;");
    if (!wg) READY();
    tag = EPOCH(); par = tag & 1;
    {
      const uint32_t lofs = (r & 1) ? (16 + 4 * (4 * w + ((r - 1) >> 1) - q)) : (16 + 4160 + 4 * (4 * w + (r >> 1) - 1 - q));
      const uint32_t pl = sb + SM_R + (5 + 2 * wg) * 16384, pa = pl + w * 4096 + ((255 - lane) ^ ((~lane & 8) >> 1)) * 16;
      uint32_t pg[4];
#pragma unroll
      for (int i = 0; i < 4; i++) { const uint32_t x = ((t128 & 112) + (lane & 1) * 8 + ((lane & 15) >> 1) - i) & 255; pg[i] = (x ^ ((x & 8) >> 1)) * 16; }
      if (lane < w) sts128(pa, make_uint4(0, 0, 0, 0));
      if (2 * w < 4 + wg) {
        const uint32_t ub = sb + offU(2 * w + 1 - wg);
        sts32(ub + 4096 + lane * 4, 0);
        if (lane < 3) sts32(ub + 8368 + lane * 4, 0);
      }
      if (warp == 7) sts32(sb + SM_ONE + lane * 4, 0x3f803f80);
      if (tid < 160) { const uint32_t c = ldg32(p.c + crank * 320 + tid * 2); sts32(sb + SM_SILU + tid * 4, pack2(silu(blo(c)), silu(bhi(c)))); }
      fence_async_s();
      bar_sync(6, 256);
      if (!wg) {
        w_arrive(BAR(B_MT));
        if (q < 2) st_relaxed2(G->st3 + ((m * 4 + n) * 2 + q) * 32 + w * 8 + r, par ^ 1, 0);
      }
      const uint32_t p0 = lane < w ? sb + SM_DUMMY + lane * 16 : pa, uo = t128 * 32 + r * 4;
      uint4* yp = G->Y + ((1 - wg) * 128 + bid) * 256 + t128;
      uint32_t A[16][4];
      auto frag = [&](bool on, uint32_t fa, int T) {
#pragma unroll
        for (int i = 0; i < 4; i++) lds32_if(on, A[T][i], fa + T * 256 + (i & 1) * 128 + (i & 2) * 32);
      };
      mbar_wait(BAR(B_FO + 1 - wg), 0);
#pragma unroll
      for (int T = 0; T < 16; T++) frag(true, sb + offF(1 - wg) + lofs, T);
#pragma unroll 1
      for (int s = 1 - wg;; s += 2) {
        float acc[128];
        const uint32_t ub = sb + offU(s), fa = sb + offF(s + 2) + lofs;
        mbar_wait(BAR(B_U + s), 0);
        const uint32_t ut = lds32(ub + uo);
        if (any_stale(ut ^ par)) { FX(118); refetch(ub + (uo & ~31), G->T + (s * 128 + bid) * 256 + (uo >> 5) * 2, uo & 31, par); }
        if (s) bar_sync(10 + wg, 256); else bar_sync(5, 128);
        TSP(1, w == 0, 10 + s);
        conv_mma(acc, A, mkdesc(ub, 64, 128, 0));
        bar_arrive(11 - wg, 256);
        mbar_wait(BAR(B_FO + min(s + 2, 4)), 0);
        WG_WAIT(0);
        TSP(1, w == 0, 15 + s);
#pragma unroll
        for (int x = 7; x >= 0; x--) {
          frag(s < 3, fa, x);
          uint32_t pk[4];
#pragma unroll
          for (int i = 0; i < 4; i++) {
            const int jj = 4 * x + i;
            float lo = acc[4 * jj], hi = acc[4 * jj + 1];
            if (jj < 31) { lo += acc[4 * jj + 6]; hi += acc[4 * jj + 7]; }
            pk[i] = pack2(lo, hi);
          }
          stsm4t(x ? pa - x * 512 : p0, pk[0], pk[1], pk[2], pk[3]);
        }
        bar_sync(4 + wg, 128);
        TSP(1, w == 0, 20 + s);
        uint4 v[8];
        auto gather = [&]() {
#pragma unroll
          for (int i = 0; i < 8; i++) v[i] = lds128(pl + (i & 3) * 4096 + (pg[i & 3] ^ ((i >> 2) * 2048)));
        };
        auto finish = [&]() {
          if (w == 1) w_count(G, C_Y + 2 * s + (bid >> 6));
#pragma unroll
          for (int e = 0; e < 2; e++) {
            const uint4 a = v[4 * e], b = v[4 * e + 1], c = v[4 * e + 2], d = v[4 * e + 3];
            yp[e * 128] = make_uint4(tagw(badd2(badd2(a.x, b.x), badd2(c.x, d.x)), par), badd2(badd2(a.y, b.y), badd2(c.y, d.y)), badd2(badd2(a.z, b.z), badd2(c.z, d.z)), badd2(badd2(a.w, b.w), badd2(c.w, d.w)));
          }
          yp += 256 * 256;
          w_arrive(BAR(s > 0 ? B_EMPTY1 - 1 + s : B_NIL));
          TSP(1, w == 0, 30 + s);
        };
        if (s >= 3) {
          const int t = min(t128, 64 + (t128 & 15));
          const uint4* mp = (const uint4*)G->modp + (t >> 4) * 32 + crank * 16 + (t & 15);
          uint32_t u[8][4];
          auto fetch = [&](bool on) {
#pragma unroll
            for (int i = 0; i < 8; i++) ldg128_if(on, mp + (i & 1) * 800 + ((i >> 1) + (i >= 6)) * 160, u[i]);
          };
          if (!wg) mbar_wait(BAR(B_YH + 5), 0);
          TSP(1, warp == 0, 61);
          fetch(warp < 3);
          gather();
          finish();
          if (warp < 3) {
#pragma unroll 1
            while (any_stale(stale(stale(stale(u[0][0] ^ par, u[1][0], par), u[2][0], par), u[3][0], par) | stale(stale(stale(u[4][0] ^ par, u[5][0], par), u[6][0], par), u[7][0], par))) fetch(true);
#pragma unroll
            for (int f = 0; f < 4; f += 2) {
              auto sum = [&](int v) { return sum2(u[v][f], u[v + 1][f], u[v][f + 1], u[v + 1][f + 1]); };
              sts128(sb + SM_MOD + (t >> 3) * 256 + (t & 3) * 64 + (t & 4) * 4 + f * 16, make_uint4(bmul2(sum(4), badd2(sum(2), 0x3f803f80)), bmul2(sum(4), sum(0)), badd2(sum(6), 0x3f803f80), 0));
            }
          }
          break;
        }
        gather();
#pragma unroll
        for (int T = 8; T < 16; T++) frag(true, fa, T);
        finish();
      }
    }
    if (!wg) { w_arrive(BAR(B_MT)); TSP(1, w == 0, 63); goto gemm; }
    asm volatile("setmaxnreg.dec.sync.aligned.u32 96;");
  } else {
    asm volatile("setmaxnreg.dec.sync.aligned.u32 96;");
    {
      uint32_t ad[8], mk[4];
#pragma unroll
      for (int x = 0; x < 8; x++) ad[x] = sb + q * 1280 + (((2 * w + (r >> 2)) ^ ((2 * q + x) & 7)) << 4) + (r & 3) * 4;
      const int pc = 255 - (bid >> 1) * 4 - q;
#pragma unroll
      for (int i = 0; i < 4; i++) mk[i] = ((pc >> 3) & 7) == (pc & 1) * 4 + i ? 0x10001u : 0u;
      uint4* d = G->T + (crank * 64 + (t128 >> 2) * 2) * 256 + pc;
      TSP(1, w == 0, 111);
      READY();
      par = EPOCH() & 1;
#pragma unroll 1
      for (int s = 0; s < 5; s++) {
        const uint32_t so = s * 16384;
        mbar_wait(BAR(B_KV + s), 0);
        TSP(1, w == 0, 1 + s); TSP(16, w == 0, 60 + s);
        if (HINT_A && s < HINT_A && w == 1) w_count(G, C_A + 2 * s + crank);
        const uint4 sk = lds128(sb + SM_S + (so >> 4) + crank * 512 + (t128 >> 2) * 16);
        uint32_t kk[11], o[8];
#pragma unroll
        for (int i = 0; i < 11; i++) kk[i] = i < 3 ? lds32(ad[i + 5] + so + (i + 5) * 128) : lds32(ad[(i - 1) & 7] + so + (i + 7) * 128);
#pragma unroll
        for (int i = 0; i < 8; i++) o[i] = lds32(ad[i] + so + KV_V + i * 128);
        const uint32_t w0 = __byte_perm(sk.x, sk.z, 0x5410), w1 = __byte_perm(sk.x, sk.z, 0x7632), w2 = __byte_perm(sk.y, sk.w, 0x5410), w3 = __byte_perm(sk.y, sk.w, 0x7632);
#pragma unroll
        for (int i = 0; i < 8; i++) o[i] = bmul2(bfma2(kk[i + 3], w0, bfma2(kk[i + 2], w1, bfma2(kk[i + 1], w2, bmul2(kk[i], w3)))), o[i]);
#pragma unroll
        for (int i = 0; i < 4; i++) o[2 * i + 1] = bitsel(o[2 * i + 1], par * 0x10001u, mk[i]);
        d[s * 32768] = make_uint4(__byte_perm(o[1], o[0], 0x5410), __byte_perm(o[3], o[2], 0x5410), __byte_perm(o[5], o[4], 0x5410), __byte_perm(o[7], o[6], 0x5410));
        d[s * 32768 + 256] = make_uint4(__byte_perm(o[1], o[0], 0x7632), __byte_perm(o[3], o[2], 0x7632), __byte_perm(o[5], o[4], 0x7632), __byte_perm(o[7], o[6], 0x7632));
        {
          if (HINT_A < 5 && s >= HINT_A && w == 1) w_count(G, C_A + 2 * s + crank);
          w_arrive(BAR(B_KVF + s));
          TSP(1, w == 0, 40 + s);
        }
      }
    }
    if (bid < 100) {
      float d[16];
      zero_acc<16>(d);
      mbar_wait(BAR(B_MT), 0);
#pragma unroll 1
      for (int s = 0; s < 5; s++) {
        const uint64_t da = mkdesc(sb + s * 16384 + (crank ^ 1) * 8192, 0, 1024, 1), db = mkdesc(sb + SM_SILU + s * 128, 16, 128, 0);
        mbar_wait(BAR(B_WM + s), 0);
        TSP(16, w == 0, 80 + s);
        WG_FENCE();
#pragma unroll
        for (int i = 0; i < 4; i++) WSS<8, 1, 0>::mma(d + i * 4, da + i * 128, db + i * 2);
        WG_COMMIT();
      }
      TSP(1, w == 0, 50);
      if (HINT_M && w == 1) w_count(G, C_M + crank);
      WG_WAIT(0);
      if (q == 0) st_relaxed2(G->modp + crank * 3200 + (bid >> 1) * 64 + w * 16 + r * 2, tagw(__float_as_uint((d[0] + d[4]) + (d[8] + d[12])), par), __float_as_uint((d[2] + d[6]) + (d[10] + d[14])));
    }
    if (w == 1 && (!HINT_M || bid >= 100)) w_count(G, C_M + crank);
    w_arrive(BAR(B_WMF));
    TSP(1, w == 0, 51);
    {
      const uint32_t qb = sb + crank * 8192 + (w * 16 + (lane & 15)) * 128 + (((lane >> 4) ^ rr) << 4);
      float red[4] = {0.f, 0.f, 0.f, 0.f};
#pragma unroll
      for (int s = 0; s < 5; s++) {
        uint32_t x[4][4];
        if (s == 0 || s == 3) { mbar_wait(BAR(B_Q + (s & 1)), 0); TSP(17, w == 0, 55 + (s & 1)); }
#pragma unroll
        for (int i = 0; i < 4; i++) ldsm4((qb ^ (i * 32)) + s * 16384, x[i][0], x[i][1], x[i][2], x[i][3]);
#pragma unroll
        for (int h = 0; h < 2; h++) {
          uint32_t su = badd2(x[0][h], x[0][h + 2]), sq = bfma2(x[0][h], x[0][h], bmul2(x[0][h + 2], x[0][h + 2]));
#pragma unroll
          for (int i = 1; i < 4; i++) { su = badd2(su, badd2(x[i][h], x[i][h + 2])); sq = bfma2(x[i][h], x[i][h], bfma2(x[i][h + 2], x[i][h + 2], sq)); }
          red[2 * h] += blo(su) + bhi(su); red[2 * h + 1] += blo(sq) + bhi(sq);
        }
      }
      TSP(1, w == 0, 57);
      bfly<4>(red, lane, 2);
      red[0] += __shfl_xor_sync(0xffffffffu, red[0], 1); red[1] += __shfl_xor_sync(0xffffffffu, red[1], 1);
      const uint32_t to = (q & 1) * peer;
      asm volatile("st.async.weak.shared::cluster.mbarrier::complete_tx::bytes.v2.f32 [%0], {%1, %2}, [%3];"
                   ::"r"(sb + SM_LN1 + ((q >> 1) * 32 + w * 8 + (r & 1) * 4 + (r >> 1)) * 16 + crank * 8 + to), "f"(red[0]), "f"(red[1]), "r"(BAR(B_LN) + to) : "memory");
      TSP(1, w == 0, 60);
    }
  }
  if (STOP_AFTER >= 2) {
    const int a = w & 1, c = w >> 1;
    const uint32_t qa = rr * 128 + ((4 * c ^ rr) << 4) + mi * 2048 + a * 1024, aa = a * 4096 + (32 * c + r) * 64 + ((q ^ (r >> 1)) << 4);
    uint32_t rs[4], ms[4];
    {
      {
        mbar_wait(BAR(B_LN), 0);
        const float4 u = lds128f(sb + SM_LN1 + a * 512 + lane * 16);
        const float mu = (u.x + u.z) * (1.f / 640.f), rq = rsqrtf(fmaxf((u.y + u.w) * (1.f / 640.f) - mu * mu, 0.f) + 1e-5f);
        const uint32_t pk = pack2(rq, -mu * rq);
#pragma unroll
        for (int j = 0; j < 4; j++) {
          const uint32_t e = __shfl_sync(0xffffffffu, pk, 8 * j + q), o = __shfl_sync(0xffffffffu, pk, 8 * j + 4 + q);
          rs[j] = __byte_perm(e, o, 0x5410); ms[j] = __byte_perm(e, o, 0x7632);
        }
        mbar_wait(BAR(B_MT), 1);
        TS1(wg == 2 ? W0(62) : 127);
      }
      uint32_t su[4] = {}, sq[4] = {};
#pragma unroll 1
      for (int s = (wg & 1) * (1 + H2); s < 5; s += (H2 && !s) ? 1 : 2) {
        const uint32_t own = sb + s * 16384 + crank * 8192;
        uint32_t x[4][4];
        mbar_wait(BAR(B_YH + s), 0);
        if (CHAIN && s > H2) bar_sync(1 + wg, 256);
        if (s == 4) TSP(2, w == 0, 99);
#pragma unroll
        for (int i = 0; i < 4; i++) ldsm4t(own + (qa ^ (i * 16)), x[i][0], x[i][1], x[i][2], x[i][3]);
        {
          const uint4 t0 = lds128(sb + SM_MOD + s * 512 + c * 256 + r * 32), t1 = lds128(sb + SM_MOD + s * 512 + c * 256 + r * 32 + 16);
          uint4 y[4];
#pragma unroll
          for (int i = 0; i < 4; i++) y[i] = lds128(sb + s * 16384 + (crank ^ 1) * 8192 + aa + i * 512);
          stage_end();
          TSP(2, w == 0, 1 + s);
#pragma unroll 1
          while (any_stale(stale(stale(stale(y[0].x ^ par, y[1].x, par), y[2].x, par), y[3].x, par))) {
            FX(120);
            int l;
            asm volatile("mov.u32 %0, %%laneid;" : "=r"(l));
#pragma unroll
            for (int i = 0; i < 4; i++) y[i] = ld_relaxed4(G->Y + (s * 128 + crank * 64 + c * 32 + i * 8 + (l >> 2)) * 256 + m * 8 + a * 4 + (l & 3));
          }
          if (CHAIN && s < 4 && s >= H2) bar_arrive(4 - wg, 256);
          w_arrive_peer(BAR(B_RF + s) + peer);
          bar_sync(wg == 1 ? 5 : 1, 128);
          TSP(2, w == 0, 10 + s);
#pragma unroll
          for (int i = 0; i < 4; i++) {
            const uint32_t yv[4] = {y[i].x, y[i].y, y[i].z, y[i].w};
            const uint32_t ca = bdup(i < 2 ? t0.x : t1.x, i & 1), sa = bdup(i < 2 ? t0.y : t1.y, i & 1), cb = bdup(i < 2 ? t0.z : t1.z, i & 1);
#pragma unroll
            for (int j = 0; j < 4; j++) x[i][j] = bfma2(bfma2(bfma2(x[i][j], rs[j], ms[j]), ca, sa), yv[j], x[i][j]);
            y[i] = make_uint4(bmul2(x[i][0], cb), bmul2(x[i][1], cb), bmul2(x[i][2], cb), bmul2(x[i][3], cb));
            sts128(own + aa + i * 512, y[i]);
          }
          const uint32_t rf = mbar_test(BAR(B_RF + s), 0);
          if (a == n >> 1) {
            uint32_t xs = sb + offX(s) - (mi + a) * 1024;
            asm volatile("" : "+r"(xs));
#pragma unroll
            for (int i = 0; i < 4; i++) stsm4t(xs + (qa ^ (i * 16)), x[i][0], x[i][1], x[i][2], x[i][3]);
          }
          if (s == 2) TSP(2, w == 0, 97);
          fence_async_s();
          w_arrive(BAR(B_AO + s));
          TSP(2, w == 0, 20 + s);
          if (any_stale(~rf)) mbar_wait(BAR(B_RF + s), 0);
          st_peer4(own + aa + peer, y, BAR(B_AP + s) + peer);
        }
        if (s == 2) TSP(2, w == 0, 98);
#pragma unroll
        for (int j = 0; j < 4; j++) {
          su[j] = badd2(su[j], badd2(badd2(x[0][j], x[1][j]), badd2(x[2][j], x[3][j])));
          sq[j] = badd2(sq[j], bfma2(x[3][j], x[3][j], bfma2(x[2][j], x[2][j], bfma2(x[1][j], x[1][j], bmul2(x[0][j], x[0][j])))));
        }
      }
      const uint32_t lb = sb + SM_LNB + w * 256 + lane * 8;
      uint2 u = make_uint2(0, 0);
      if (wg == 2 - H2) { mbar_wait(BAR(B_LNB), 0); u = lds64(lb); }
      float red[8];
#pragma unroll
      for (int k = 0; k < 4; k++) {
        const uint32_t lo = (k & 1) ? sq[k >> 1] : su[k >> 1], hi = (k & 1) ? sq[2 + (k >> 1)] : su[2 + (k >> 1)];
        const uint32_t mine = (lane & 16) ? hi : lo, other = __shfl_xor_sync(0xffffffffu, (lane & 16) ? lo : hi, 16);
        red[(k >> 1) * 4 + (k & 1)] = blo(mine) + blo(other); red[(k >> 1) * 4 + 2 + (k & 1)] = bhi(mine) + bhi(other);
      }
      bfly<8>(red, lane, 8); bfly<4>(red, lane, 4);
      if (wg == 1 + H2) { sts64(lb, __float_as_uint(red[0]), __float_as_uint(red[1])); w_arrive(BAR(B_LNB)); }
      else {
        const uint32_t la = sb + SM_LN2 + (a * 16 + (q >> 1) * 8 + r) * 64 + (q & 1) * 8 + (crank * 2 + c) * 16;
#pragma unroll
        for (int i = 0; i < 2; i++)
          asm volatile("st.async.weak.shared::cluster.mbarrier::complete_tx::bytes.v2.f32 [%0], {%1, %2}, [%3];" ::"r"(la + i * peer), "f"(red[0] + __uint_as_float(u.x)), "f"(red[1] + __uint_as_float(u.y)), "r"(BAR(B_LN + 1) + i * peer) : "memory");
        TSP(2, w == 0, 30);
      }
    }
  }
  if (wg == 2) {
    if (STOP_AFTER >= 3) {
      constexpr int TT = 128 / VT, NK = 7 * VT;
      const uint32_t to = (t128 & (TT - 1)) * 32 + r * 4;
      uint32_t off = (w * VT >> 2) * 8, ph = 0;
#pragma unroll 1
      for (int i = w * VT >> 2; i < 32; i += VT) {
        const uint32_t tb = sb + (((uint32_t)(0x9874245000ull >> off) & 255) << 10), vb = BAR(B_VAL) + off;
        if (VT > 1) mbar_wait(vb, ph ^ 1);
        mbar_wait(vb - (B_VAL - B_FULL2) * 8, ph);
        TSP(8, (w * VT & 3) == 0 && i < 15, 41 + i);
        uint32_t b0 = 0, b1 = 0, b2 = 0;
#pragma unroll
        for (int k = 0; k < NK; k++) { uint32_t& b = k % 3 == 0 ? b0 : k % 3 == 1 ? b1 : b2; b = stale(b, lds32(tb + to + k * TT * 32), par); }
        off += 8 * VT;
        if (off >= 40) { off -= 40; ph ^= 1; }
        if (any_stale(b0 | b1 | b2)) {
          FX(121);
#pragma unroll 1
          for (int k = 0; k < NK; k++) refetch(tb + (to & ~31) + k * TT * 32, G->z2n + (n * 32 + (i & 16) + ((i + ROT * (m >> 3)) & 15)) * IMG + k * TT * 2 + (to >> 5) * 2, r * 4, par);
        }
        asm volatile(ELECT "mbarrier.arrive.shared::cta.b64 _, [%0], %1;\n}" ::"r"(vb), "n"(VT) : "memory");
        TSP(8, (w * VT & 3) == 0 && i < 15, 61 + i);
      }
    }
    goto done;
  }
  asm volatile("setmaxnreg.inc.sync.aligned.u32 192;");
gemm:
  {
    if (STOP_AFTER >= 2) {
      const uint32_t za = sb + SM_PO + (mi >> 1) * 1024 + (16 * w + (mi & 1) * 8 + rr) * 16;
      const bool shifted = !wg ^ (n == 1);
      const int R0 = (m >> 1) * 128 + (m & 1) * 32 + w * 8 + r;
      const uint32_t bs0 = q ? 0 : ldg16(p.bsp + R0), bs1 = q ? 0 : ldg16(p.bsp + R0 + 64);
      float k10, k11, sg0 = 0.f, sg1 = 0.f;
      uint32_t zb[28] = {};
      const uint2* sp = G->st3 + (m * 4 + q) * 64 + w * 8 + r;
      uint2 s3 = make_uint2(0, 0);
      uint32_t* const px = (uint32_t*)(G->z2n + (n * 32 + (m >> 1)) * IMG + (shifted ? 256 : 0) + (m & 1) * 32 + w * 8) + lane;
      uint32_t* const py = px - (shifted ? 7168 : 0);
      auto put = [&](bool on, int h, int j, uint32_t v) { stg32_if(on, (j < 24 ? px : py) + h * 16 * IMG * 4 + j * 256, v); };
      const uint32_t tg = rr == (m & 1) * 4 + w;
      {
        float z[112];
        undef<112>(z);
        float k20, k21;
        {
          bar_sync(wg ? 7 : 10, 256);
#pragma unroll 1
          for (int t = 0; t < 10; t += 2) {
            const int g = wg * 10 + t;
            const uint32_t sx = opaque(sb);
            const uint64_t db = mkdesc(sx + SM_R + (g & 2) * 32768, 8192, 1024, 1), da = mkdesc(sx + t * 8192, 4096, 512, 2), dn = mkdesc(sx + SM_R + (g & 2) * 32768 + 24576, 0, 512, 2);
            const uint32_t fb = BAR(B_FULL1 + (g & 2)), e0 = BAR(t ? B_EMPTY1 + 3 - (g & 2) : B_NIL), x0 = BAR(g == 14 ? B_EMPTY2 : g == 18 ? B_EMPTY2 + 2 : B_NIL), x1 = BAR(g >= 16 ? B_EMPTY2 - 15 + g : B_NIL);
#pragma unroll
            for (int j = 0; j < 2; j++) {
              const uint64_t dx = da + (j ^ crank) * 512;
              mbar_wait2(fb + j * 8, BAR(j ? B_AP : B_AO) + t * 4, (g >> 2) & 1, 0);
              if (GATE > 0 && j == (GATE & 1) && g == 10 + (GATE & ~1)) bar_sync(8, 256);
              TSP(2, w == 0, 40 + g + j);
              WG_FENCE();
#pragma unroll
              for (int i = 0; i < 4; i++) WSS<32, 1, 1>::mma(z + 96, dx + i * 64, dn + j * 2048 + i * 64, i || j || t);
#pragma unroll
              for (int i = 0; i < 4; i++) WSS<192, 1, 1>::mma(z, dx + i * 64, db + j * 2048 + i * 128, i || j || t);
              WG_COMMIT();
              WG_WAIT(1);
              if (lane == 0) { mbar_arrive(j ? fb + (B_EMPTY1 - B_FULL1) * 8 : e0); mbar_arrive(j ? x1 : x0); }
            }
          }
          if (!wg && GATE) bar_arrive(7, 256);
          mbar_wait(BAR(B_LN + 1), 0);
          TSP(2, w == 0, 60 + wg);
          const float4 y = lds128f(sb + SM_LN2 + t128 * 16);
          const float m0 = quad_sum(y.x) * (1.f / 640.f), m1 = quad_sum(y.z) * (1.f / 640.f);
          const float v0 = fmaxf(quad_sum(y.y) * (1.f / 640.f) - m0 * m0, 0.f) + 1e-5f, v1 = fmaxf(quad_sum(y.w) * (1.f / 640.f) - m1 * m1, 0.f) + 1e-5f;
          const float h0 = rsqrtf(v0), h1 = rsqrtf(v1);
          sg0 = v0 * h0; sg1 = v1 * h1; k10 = h0 * 0.7978845608028f; k11 = h1 * 0.7978845608028f; k20 = h0 * h0 * h0 * 0.0356774081363f; k21 = h1 * h1 * h1 * 0.0356774081363f;
          const uint32_t ext[4] = {ext_frag(m0, sg0, q), ext_frag(m1, sg1, q), 0u, 0u};
          const uint64_t dv = mkdesc(sb + SM_VT, 0, 128, 0);
          if (wg) mbar_wait(BAR(B_VTF), 0);
          mbar_wait(BAR(B_VT), wg);
          WG_FENCE();
          WRS<32>::mma(z + 96, ext, dv + (shifted ? 0 : 192)); WRS<192>::mma(z, ext, dv + (shifted ? 32 : 0));
          WG_COMMIT();
          if (!wg && GATE >= 0) bar_arrive(GATE ? 8 : 7, 256);
          WG_WAIT(1);
          if (lane == 0) mbar_arrive(BAR(wg ? B_EMPTY2 + 4 : B_EMPTY1 + 1));
          WG_WAIT(0);
          if (wg) bar_sync(5, 128); else if (lane == 0) mbar_arrive(BAR(B_VTF));
          TSP(2, w == 0, 62 + wg);
        }
        if (!wg) {
          uint32_t z0[28];
#pragma unroll
          for (int h = 0; h < 2; h++) {
            float s0, q0, s1, q1, s2, q2;
#pragma unroll
            for (int j = 0; j < 28; j++) {
              if (j == LOAD_AT && h) s3 = ld_relaxed2(sp);
              if (j == PUB_AT && h) {
#pragma unroll 1
                while (any_stale(s3.x ^ par)) { FX(119); s3 = ld_relaxed2(sp); }
                TSP(2, w == 0, 68);
                const uint32_t cp = ln3(quad_sum(__uint_as_float(s3.x)), quad_sum(__uint_as_float(s3.y)), 4e-5f * sg0 * sg0);
#pragma unroll
                for (int i = 0; i < 28; i++) put(true, 0, i, bitsel(baffine(z0[i], cp), par, tg));
                TSP(2, w == 0, 70);
              }
              const float a = gelu2(z[4 * j + 2 * h], h ? k11 : k10, h ? k21 : k20), b = gelu2(z[4 * j + 2 * h + 1], h ? k11 : k10, h ? k21 : k20);
              (h ? zb : z0)[j] = pack2(a, b);
              if (j == 0) { s0 = a; s1 = b; q0 = a * a; q1 = b * b; }
              else { s0 += a; s1 += b; q0 = fmaf(a, a, q0); q1 = fmaf(b, b, q1); }
              if (j == 23) { s2 = s0 + s1; q2 = q0 + q1; }
              if (h && j % PSTEP == PSTEP - 1) stage_end();
            }
            s0 = quad_sum(n == 3 ? s2 : s0 + s1); q0 = quad_sum(n == 3 ? q2 : q0 + q1);
            if (q == n) st_relaxed2((uint2*)sp + h * 32, tagw(__float_as_uint(s0), par), __float_as_uint(q0));
            if (!h && w == 1) { w_count_timed(G, C_G + crank); w_arrive(BAR(B_G0)); }
            TSP(2, w == 0, 64 + h);
            stage_end();
          }
          sts32(sb + SM_LNB + t128, __float_as_uint(4e-5f * sg1 * sg1), q == 0);
          w_arrive(BAR(B_G1));
          if (STOP_AFTER < 3) {
            mbar_wait(BAR(B_CP), 0);
            const uint32_t cp = lds32(sb + SM_LNB + (t128 & ~3));
#pragma unroll
            for (int j = 0; j < 28; j++) put(true, 1, j, bitsel(baffine(zb[j], cp), par, tg));
            w_arrive(BAR(B_PUB));
          }
        } else if (STOP_AFTER >= 3) {
          uint32_t zx = za + (shifted ? 4096 : 0), zy = za - (shifted ? 24576 : 0);
          asm volatile("" : "+r"(zx), "+r"(zy));
#pragma unroll
          for (int j = 0; j < 28; j += 2) stsm4((j < 24 ? zx : zy) + j * 1024, pack2(z[4 * j], z[4 * j + 1]), pack2(z[4 * j + 2], z[4 * j + 3]), pack2(z[4 * j + 4], z[4 * j + 5]), pack2(z[4 * j + 6], z[4 * j + 7]));
          __syncwarp();
          TSP(2, w == 0, 66);
#pragma unroll 1
          for (int j = 0; j < 14; j++) {
            const float cs = n == 3 && j < 2 ? 0.f : 0.5f / 0.7978845608028f, c0 = k10 * cs, c1 = k11 * cs;
            uint32_t v[4];
            ldsm4(za + j * 2048, v[0], v[1], v[2], v[3]);
#pragma unroll
            for (int i = 0; i < 4; i++) v[i] = pack2(gelu2(blo(v[i]), (i & 1) ? k11 : k10, (i & 1) ? k21 : k20) * ((i & 1) ? c1 : c0), gelu2(bhi(v[i]), (i & 1) ? k11 : k10, (i & 1) ? k21 : k20) * ((i & 1) ? c1 : c0));
            stsm4(za + j * 2048, v[0], v[1], v[2], v[3]);
          }
          w_arrive(BAR(B_Z1S));
        }
        TSP(2, w == 0, 72 + wg);
      }
      if (STOP_AFTER >= 3) {
        if (!wg) {
          float g[112];
          uint32_t cp = 0;
          auto step = [&](uint64_t da, uint64_t db, uint32_t rel) {
            WG_FENCE();
#pragma unroll
            for (int j = 0; j < 8; j++) {
              if (j < 4) WSS<128, 0, 1>::mma(g, da + j * 2, db + j * 16); else WSS<96, 0, 1>::mma(g + 64, da + j * 2 - 8, db + j * 16 + 960);
              if (j == RELJ) { WG_COMMIT(); WG_WAIT(1); if (lane == 0) mbar_arrive(rel); if (j < 7) WG_FENCE(); }
            }
            if (RELJ < 7) WG_COMMIT();
          };
          {
            const uint32_t bias[4] = {bs0, bs1, 0u, 0u};
            WG_FENCE();
            wrs96_first(g + 64, bias, mkdesc(sb + SM_ONE, 0, 0, 0)); wrs128_first(g, bias, mkdesc(sb + SM_ONE, 0, 0, 0));
            WG_COMMIT();
          }
#pragma unroll 1
          for (int rnd = 0;; rnd++) {
            const uint32_t sx = opaque(sb);
            const uint64_t dA2 = mkdesc(sx, 16, 1024, 1), dB2 = mkdesc(sx, 128, 1024, 0);
            const uint32_t fb = BAR(B_VAL), e0 = BAR(rnd ? B_EMPTY2 + 4 : B_NIL);
#pragma unroll
            for (int st = 0; st < 5; st++) {
              const uint64_t da = dA2 + (placeA(st) >> 4), db = dB2 + (placeB(st) >> 4);
              TSP(8, w == 0, rnd * 5 + st + 1);
              mbar_wait(fb + st * 8, rnd & 1);
              TSP(8, w == 0, rnd * 5 + st + 21);
              if (st == 0 || rnd == 0) TSP(4, w == 0, st ? 10 + st : 1 + rnd);
              step(da, db, st ? BAR(B_EMPTY2 + st - 1) : e0);
#pragma unroll
              for (int j = 6 * st; j < min(6 * st + 6, 28); j++) put(rnd == (st < 2), 1, j, bitsel(baffine(zb[j], cp), par, tg));
              if (st == 1) { if (rnd) goto g2_main; mbar_wait(BAR(B_CP), 0); cp = lds32(sb + SM_LNB + (t128 & ~3)); }
            }
          }
        g2_main:
          w_arrive(BAR(B_PUB));
          uint32_t z1[56];
#pragma unroll
          for (int i = 0; i < 56; i++) z1[i] = i < 28 ? zb[i] : ZINIT;
          const uint32_t zl = __shfl_sync(0xffffffffu, za, lane);
          uint32_t ph = 1;
          uint64_t dA2 = mkdesc(sb, 16, 1024, 1), dB2 = mkdesc(sb, 128, 1024, 0);
#pragma unroll 1
          for (int rnd = 1; rnd < 6; rnd++, ph ^= 1) {
            asm volatile("" : "+l"(dA2), "+l"(dB2));
#pragma unroll
            for (int k = 0; k < 5; k++) {
              const int st = (k + 2) % 5;
              const uint64_t da = dA2 + (placeA(st) >> 4), db = dB2 + (placeB(st) >> 4);
              TSP(8, w == 0 && rnd * 5 + k < 13, rnd * 5 + k + 3);
              if (k != 1) mbar_wait(BAR(B_VAL + st), k > 2 ? ph ^ 1 : ph); else mbar_wait2(BAR(B_VAL + st), BAR(rnd == 3 ? B_Z1S : B_CP), ph, 0);
              TSP(8, w == 0 && rnd * 5 + k < 13, rnd * 5 + k + 23);
              if (st == 0) TSP(4, w == 0, 2 + rnd); else TSP(4, w == 0, 95 + st);
              step(da, db, BAR(B_EMPTY2 + (k + 1) % 5));
#pragma unroll
              for (int j = 0; j < 3; j++) if (5 * j + k) ldsm4_if(rnd == 3 + j, zl + (5 * j + k - 1) * 2048, z1 + 4 * (5 * j + k - 1));
            }
          }
          TSP(4, w == 0, 100);
          w_arrive_peer(BAR(B_PFREE) + peer);
          if (STOP_AFTER >= 4) bar_arrive(13, 256);
          WG_WAIT(0);
          if (lane == 0) mbar_arrive(BAR(B_EMPTY2 + 1));
          TSP(4, w == 0, 20);
          stage_end();
#pragma unroll
          for (int j = 0; j < 28; j += 2) {
#pragma unroll
            for (int i = 2 * j; i < 2 * j + 4; i++) z1[i] = bmul2(z1[i], pack2(g[2 * i], g[2 * i + 1]));
            stsm4(zl + j * 1024, z1[2 * j], z1[2 * j + 1], z1[2 * j + 2], z1[2 * j + 3]);
            if ((j == 12 && !PONE) || j == 26) { fence_async_s(); w_arrive(BAR(B_PST + (j >> 4))); TSP(4, w == 0, 21 + (j >> 4)); stage_end(); }
          }
        }
      }
      if (STOP_AFTER >= 4) {
        float o[64];
        undef<64>(o);
        mbar_wait(BAR(B_GB), 0);
#pragma unroll 1
        for (int it = 0; it <= wg; it++) {
          const int box = it ? 4 : (2 - 2 * wg) ^ (n & BOXX);
          uint4 gb[4];
#pragma unroll
          for (int i = 0; i < 4; i++) gb[i] = lds128(sb + SM_GB + box * 128 + i * 64 + q * 16);
#pragma unroll 1
          for (int t = 0; t < 2; t++) {
            const uint32_t sx = opaque(sb);
            const uint64_t da = mkdesc(sx + (t ? 0 : SM_PO), 1024, 128, 0);
            if (!(it & t)) bar_sync(12 + wg, 256);
            if (!it) {
              const uint32_t f0 = BAR(B_FULL2 + 4 - 2 * wg), f1 = BAR(B_FULL2 + 1 + 2 * wg), pb = BAR(t ? B_PP : B_PST);
#pragma unroll
              for (int j = 0; j < 2; j++) {
                const uint64_t db = mkdesc(sx + (wg ? placeB(2 + j) : placeB(4 - 3 * j)), 14336, 1024, 1);
                mbar_wait2(j ? f1 : f0, pb + (j || (PONE && !t)) * 8, t ^ (j & ~wg), 0);
                TSP(4, w == 0, 32 - 2 * wg + 4 * t + j);
                WG_FENCE();
#pragma unroll
                for (int i = 0; i < 7; i++) WSS<128, 0, 1>::mma(o, da + j * 896 + i * 128, db + i * 128, i || j || t);
                WG_COMMIT();
              }
              bar_arrive(13 - wg, 256);
              WG_WAIT(1);
              if (lane == 0) mbar_arrive(f0 + (B_EMPTY2 - B_FULL2) * 8);
              WG_WAIT(0);
              if (lane == 0) mbar_arrive(f1 + (B_EMPTY2 - B_FULL2) * 8);
            } else {
              const uint64_t db = mkdesc(sx + (t ? placeB(3) : placeB(2)), 0, 1024, 1);
              mbar_wait(BAR(B_FULL2 + 2 + t), 0);
              TSP(4, w == 0, 38 + t);
              WG_FENCE();
#pragma unroll
              for (int i = 0; i < 14; i++) WSS<64, 0, 1>::mma(o, da + i * 128, db + i * 128, i || t);
              WG_COMMIT();
            }
          }
          if (it == wg) w_arrive(BAR(B_DONE + wg));
          WG_WAIT(0);
          TSP(4, w == 0, 40 + it + 2 * !wg);
#pragma unroll
          for (int b = 0; b < 2; b++) {
            const uint32_t ob = sb + placeA(box + b) + w * 2048, oa = ob + (lane & 15) * 128 + (((mi >> 1) ^ rr) << 4);
#pragma unroll
            for (int i = 0; i < 4; i++) {
              const float* a = o + b * 32 + i * 8;
              const uint4 gq = gb[2 * b + (i >> 1)];
              const uint32_t g0 = (i & 1) ? gq.z : gq.x, g1 = (i & 1) ? gq.w : gq.y;
              stsm4(oa ^ (i * 32), bmul2(pack2(a[0], a[1]), g0), bmul2(pack2(a[2], a[3]), g0), bmul2(pack2(a[4], a[5]), g1), bmul2(pack2(a[6], a[7]), g1));
            }
            fence_async_s();
            __syncwarp();
            tma_rows_add(&tm.out, (box + b) * 128 + crank * 64, m & ~1, (m & 1) * 4 + w, ob);
            TSP(4, w == 0, 50 + box + b);
            if (it) break;
          }
        }
        bulk_commit();
        bulk_wait_read0();
        TSP(4, w == 0, 56 + wg);
        return;
      }
    }
  }
done:
  w_arrive(BAR(B_DONE + wg));
}

typedef CUresult (*EncodeFn)(CUtensorMap*, CUtensorMapDataType, cuuint32_t, void*, const cuuint64_t*, const cuuint64_t*, const cuuint32_t*, const cuuint32_t*,
                             CUtensorMapInterleave, CUtensorMapSwizzle, CUtensorMapL2promotion, CUtensorMapFloatOOBfill);
struct Dim { uint64_t size, stride; uint32_t box; };

CUtensorMap make_map(EncodeFn enc, const void* ptr, uint64_t cols, Dim a, Dim b = {0, 0, 0}, Dim c = {0, 0, 0}, Dim d = {0, 0, 0}, uint32_t width = 64) {
  CUtensorMap m;
  cuuint64_t gd[5] = {cols, a.size, b.size, c.size, d.size}, gs[4] = {a.stride, b.stride, c.stride, d.stride};
  cuuint32_t bd[5] = {width, a.box, b.box, c.box, d.box}, es[5] = {1, 1, 1, 1, 1};
  enc(&m, CU_TENSOR_MAP_DATA_TYPE_BFLOAT16, d.size ? 5 : c.size ? 4 : b.size ? 3 : 2, const_cast<void*>(ptr), gd, gs, bd, es, CU_TENSOR_MAP_INTERLEAVE_NONE,
      width == 64 ? CU_TENSOR_MAP_SWIZZLE_128B : width == 32 ? CU_TENSOR_MAP_SWIZZLE_64B : CU_TENSOR_MAP_SWIZZLE_NONE, CU_TENSOR_MAP_L2_PROMOTION_L2_128B, CU_TENSOR_MAP_FLOAT_OOB_FILL_NONE);
  return m;
}

}

extern "C" void kernel_launch(void* const* d_in, const int* in_sizes, int n_in, void* d_out, int out_size) {
  (void)in_sizes; (void)n_in; (void)out_size;
  void* fn = nullptr;
  cudaDriverEntryPointQueryResult qr;
  cudaGetDriverEntryPoint("cuTensorMapEncodeTiled", &fn, cudaEnableDefault, &qr);
  EncodeFn enc = (EncodeFn)fn;
  Params p;
  p.k = (const __nv_bfloat16*)d_in[1]; p.v = (const __nv_bfloat16*)d_in[2];
  p.shiftk = (const __nv_bfloat16*)d_in[3]; p.ssmD = (const __nv_bfloat16*)d_in[5];
  p.bsp = (const __nv_bfloat16*)d_in[9]; p.c = (const __nv_bfloat16*)d_in[11]; p.wout = (const __nv_bfloat16*)d_in[10];
  p.wsp = (const __nv_bfloat16*)d_in[8];
  void* scr = nullptr;
  cudaGetSymbolAddress(&scr, g_scr);
  p.g = (Scratch*)scr;
  int dev = 0, nsm = 0;
  cudaGetDevice(&dev);
  cudaDeviceGetAttribute(&nsm, cudaDevAttrMultiProcessorCount, dev);
  p.by_sm = nsm == 132;
  for (int t = 0; t < 64; t++) {
    const int grp = t < 32 ? t & 7 : t < 60 ? (t - 32) % 7 + 1 : 0, i = t < 32 ? t >> 3 : t < 60 ? 4 + (t - 32) / 7 : t - 56;
    p.tile[t] = ((grp >> 1) * 8 + i) * 2 + (grp & 1);
  }
  const Dim one = {1, 16, 1};
  Maps tm;
  tm.k = make_map(enc, d_in[1], 640, {8, 1280, 10}, {256, 10240, 5}, one, one);
  tm.v = make_map(enc, d_in[2], 640, {8, 1280, 10}, {256, 10240, 4}, one, one);
  tm.f = make_map(enc, d_in[4], 256, {8, 512, 8}, {640, 4096, 1}, one, one, 256);
  tm.wm = make_map(enc, d_in[12], 3840, {640, 7680, 64}, one, one, one);
  tm.q = make_map(enc, d_in[0], 640, {2, 1280, 2}, {32, 81920, 2}, {8, 10240, 4}, {4, 2560, 4});
  tm.y = make_map(enc, p.g->Y, 32, {640, 4096, 64}, {64, 64, 2}, {0, 0, 0}, {0, 0, 0}, 32);
  tm.wm2 = make_map(enc, d_in[12], 64, {640, 7680, 64}, {60, 128, 2});
  tm.w3 = make_map(enc, d_in[7], 64, {640, 3456, 64}, {27, 128, 3});
  tm.wn = make_map(enc, d_in[7], 1728, {640, 3456, 64}, {0, 0, 0}, {0, 0, 0}, {0, 0, 0}, 32);
  tm.w2 = make_map(enc, d_in[7], 64, {640, 3456, 64}, {27, 128, 2});
  tm.wsp = make_map(enc, d_in[8], 2048, {8, 4096, 8}, {32, 262144, 2}, {8, 32768, 4});
  tm.x1 = make_map(enc, d_out, 640, {2, 1280, 2}, {32, 81920, 2}, {8, 10240, 2}, {4, 2560, 4});
  tm.out = make_map(enc, d_out, 640, {8, 1280, 8}, {32, 81920, 2}, {8, 10240, 1});
  tm.wo = make_map(enc, d_in[10], 640, {864, 1280, 112});
  cudaFuncSetAttribute(fused_kernel, cudaFuncAttributeMaxDynamicSharedMemorySize, SM_TOTAL);
  cudaLaunchConfig_t cfg = {};
  cfg.gridDim = dim3(132); cfg.blockDim = dim3(512); cfg.dynamicSmemBytes = SM_TOTAL; cfg.stream = cudaStreamPerThread;
  cudaLaunchAttribute at[1];
  at[0].id = cudaLaunchAttributeCooperative; at[0].val.cooperative = 1;
  cfg.attrs = at; cfg.numAttrs = 1;
  cudaLaunchKernelEx(&cfg, fused_kernel, p, tm);
}
```
